```python
import torch

def _softmax(x, axis=-1):
    return torch.softmax(x, dim=axis)
def _gelu(x):
    return torch.nn.functional.gelu(x, approximate="tanh")
def _silu(x):
    return torch.nn.functional.silu(x)
def _sigmoid(x):
    return torch.sigmoid(x)
def _layernorm(x, axis=-1, eps=1e-5):
    m = x.mean(dim=axis, keepdim=True)
    v = x.var(dim=axis, keepdim=True, unbiased=False)
    return (x - m) / torch.sqrt(v + eps)
def _scatter_add(tgt, idx, src, axis=0):
    return tgt.clone().index_add_(axis, idx, src)
def _segment_sum(src, seg, n):
    out = torch.zeros((n,) + src.shape[1:], dtype=src.dtype)
    return out.index_add_(0, seg, src)
def _pad(x, pw):
    flat = tuple(v for pair in reversed(pw) for v in pair)
    return torch.nn.functional.pad(x, flat)

kernel_name = 'parallel_sum__ssm_conv_h3__glu_gated_reglu__prompt'

def setup_inputs():

    _w = (lambda a: (lambda t: t.to(torch.bfloat16) if t.is_floating_point() else t)(torch.as_tensor(a)))
    def _A_setup():
        B, S, D = 1, 2048, 448
        ks = 4
        return {
            "q": _w((lambda *s: torch.randn(*s, dtype=torch.bfloat16) * 0.05)(B, S, D)),
            "k": _w((lambda *s: torch.randn(*s, dtype=torch.bfloat16) * 0.2)(B, S, D)),
            "v": _w((lambda *s: torch.randn(*s, dtype=torch.bfloat16) * 0.2)(B, S, D)),
            "shift_k": _w((lambda *s: torch.randn(*s, dtype=torch.bfloat16) * 0.2)(D, ks) * 0.5),
            "ssm_k": _w((lambda *s: torch.randn(*s, dtype=torch.bfloat16) * 0.4)(D, S) * (1.0 / S ** 0.5)),
            "ssm_D": _w((lambda *s: torch.randn(*s, dtype=torch.bfloat16) * 0.2)(D)),
        }
    _A_in = _A_setup()

    def _B_setup():
        B, S, D, F = 1, 2048, 448, 1792
        return {
            "x": _w((lambda *s: torch.randn(*s, dtype=torch.bfloat16) * 0.05)(B, S, D)),
            "W_gate": _w((lambda *s: torch.randn(*s, dtype=torch.bfloat16) * 0.2)(D, F) * (2.0 / D) ** 0.5),
            "W_up": _w((lambda *s: torch.randn(*s, dtype=torch.bfloat16) * 0.2)(D, F) * (2.0 / D) ** 0.5),
            "W_down": _w((lambda *s: torch.randn(*s, dtype=torch.bfloat16) * 0.2)(F, D) * (1.0 / F) ** 0.5),
        }
    _B_in = _B_setup()

    return {
        "A_q": _A_in["q"],
        "A_k": _A_in["k"],
        "A_v": _A_in["v"],
        "A_shift_k": _A_in["shift_k"],
        "A_ssm_k": _A_in["ssm_k"],
        "A_ssm_D": _A_in["ssm_D"],
        "B_x": _B_in["x"],
        "B_W_gate": _B_in["W_gate"],
        "B_W_up": _B_in["W_up"],
        "B_W_down": _B_in["W_down"],
    }

def reference(A_q, A_k, A_v, A_shift_k, A_ssm_k, A_ssm_D, B_x, B_W_gate, B_W_up, B_W_down):
    def _A_ref(q, k, v, shift_k, ssm_k, ssm_D):
        B, S, D = q.shape
        ks = shift_k.shape[-1]
        k_pad = _pad(k, ((0, 0), (ks - 1, 0), (0, 0)))
        k_shift = torch.zeros_like(k)
        for t in range(ks):
            k_shift = k_shift + k_pad[:, t:t + S, :] * shift_k[:, ks - 1 - t][None, None, :]
        kv = k_shift * v
        L = 2 * S
        kv_pad = _pad(kv, ((0, 0), (0, S), (0, 0)))
        kf_pad = _pad(ssm_k, ((0, 0), (0, S)))
        kv_f = (lambda x, axes=(-2,-1): torch.fft.rfft2(x.float(), dim=axes))(kv_pad[:, None, :, :], axes=(1, 2))
        kf_f = (lambda x, axes=(-2,-1): torch.fft.rfft2(x.float(), dim=axes))(kf_pad[:, None, :], axes=(1, 2))
        kf_f = (lambda x, *d: x.permute(*d))(kf_f, 1, 2, 0)
        y_f = kv_f * kf_f[None, :, :, :]
        y = (lambda x, s, axes=(-2,-1): torch.fft.irfft2(x, s=s, dim=axes).to(torch.bfloat16))(y_f, (1, L), axes=(1, 2))[:, 0, :S, :]
        y = y + kv * ssm_D[None, None, :]
        return q * y

    def _B_ref(x, W_gate, W_up, W_down):
        gate = torch.einsum("bsd,df->bsf", x, W_gate)
        up = torch.einsum("bsd,df->bsf", x, W_up)
        gate = gate * (lambda x, dt: x.to(dt))(gate > 0, gate.dtype)
        h = gate * up
        return torch.einsum("bsf,fd->bsd", h, W_down)

    x = A_q
    xn = _layernorm(x, axis=-1)
    return x + _A_ref(xn, A_k, A_v, A_shift_k, A_ssm_k, A_ssm_D) + _B_ref(xn, B_W_gate, B_W_up, B_W_down)
```

```cpp
#include <cuda_runtime.h>
#include <cuda_bf16.h>
#include <cuda.h>
#include <stdint.h>

namespace {

constexpr int S_LEN = 2048;
constexpr int D_DIM = 448;
constexpr int F_DIM = 1792;
constexpr int NCTA  = 128;
constexpr int NTHREADS = 384;
constexpr int CONV_CTAS = 112;

constexpr uint32_t SLOT_BYTES = 32768;
constexpr int      NSLOT      = 5;
constexpr uint32_t OFF_RING = 0;
constexpr uint32_t OFF_HST  = NSLOT * SLOT_BYTES;
constexpr uint32_t OFF_C    = OFF_HST + 16384;
constexpr uint32_t U_BYTES  = 4352;
constexpr uint32_t HC_BYTES = 8320;
constexpr uint32_t HC_COPY0 = 4160;
constexpr uint32_t OFF_U    = OFF_C;
constexpr uint32_t OFF_HC   = OFF_C + 4 * U_BYTES;
constexpr uint32_t OFF_KST  = OFF_U;
constexpr uint32_t OFF_VTAIL = 28672;
constexpr uint32_t OFF_MISC = OFF_HC + 4 * HC_BYTES;
constexpr uint32_t OFF_BAR  = OFF_MISC;
constexpr uint32_t OFF_DV   = OFF_MISC + 256;
constexpr uint32_t OFF_STAT = OFF_MISC + 512;
constexpr uint32_t SMEM_BYTES = OFF_STAT + 1024;
static_assert(SMEM_BYTES <= 232448, "smem");

constexpr int B_FULL = 0, B_EMPTY = 5, B_XFULL = 10, B_HRAW = 17, B_CONVRDY = 18, B_EPIFULL = 19, B_CONVDONE = 20,
              B_HSTF = 21, B_HSTE = 23, B_YFULL = 25, B_KVFULL = 26;

struct alignas(64) Params {
  CUtensorMap tm_x;
  CUtensorMap tm_wg;
  CUtensorMap tm_wu;
  CUtensorMap tm_hs;
  CUtensorMap tm_hh;
  CUtensorMap tm_hl;
  CUtensorMap tm_wd;
  CUtensorMap tm_xe;
  CUtensorMap tm_y;
  CUtensorMap tm_out;
  const __nv_bfloat16* k;
  const __nv_bfloat16* v;
  const __nv_bfloat16* shift_k;
  const __nv_bfloat16* ssm_k;
  const __nv_bfloat16* ssm_D;
  const __nv_bfloat16* wg;
  const __nv_bfloat16* wu;
  const __nv_bfloat16* wd;
  __nv_bfloat16* out;
};

__device__ __align__(1024) __nv_bfloat16 g_h[S_LEN * F_DIM];
__device__ __align__(1024) __nv_bfloat16 g_kvT[D_DIM * S_LEN];
__device__ __align__(1024) __nv_bfloat16 g_y2T[D_DIM * S_LEN];
__device__ __align__(1024) uint4 g_part[NCTA * 7 * 128];
struct Sync {
  unsigned epoch;      unsigned pad0[31];
  unsigned cnt_kv;     unsigned pad1[31];
  unsigned cnt_h[32 * 32];
  unsigned cnt_y[4 * 32];
  unsigned xflag[NCTA * 32];
};
__device__ __align__(1024) Sync g_sync;

__device__ __forceinline__ uint32_t smem_u32(const void* p) { return (uint32_t)__cvta_generic_to_shared(p); }
__device__ __forceinline__ void mbar_init(uint32_t a, uint32_t c) { asm volatile("mbarrier.init.shared::cta.b64 [%0], %1;" ::"r"(a), "r"(c)); }
__device__ __forceinline__ void mbar_expect_tx(uint32_t a, uint32_t bytes) {
  asm volatile("mbarrier.arrive.expect_tx.shared::cta.b64 _, [%0], %1;" ::"r"(a), "r"(bytes) : "memory");
}
__device__ __forceinline__ void mbar_arrive(uint32_t a) { asm volatile("mbarrier.arrive.shared::cta.b64 _, [%0];" ::"r"(a) : "memory"); }
__device__ __forceinline__ void mbar_arrive_cta(uint32_t a, uint32_t cta) {
  asm volatile("{\n.reg .b32 r;\nmapa.shared::cluster.u32 r, %0, %1;\nmbarrier.arrive.shared::cluster.b64 _, [r];\n}" ::"r"(a), "r"(cta) : "memory");
}
__device__ __forceinline__ bool mbar_try(uint32_t a, uint32_t ph) {
  uint32_t ok;
  asm volatile("{\n.reg .pred p;\nmbarrier.try_wait.parity.shared::cta.b64 p, [%1], %2;\nselp.u32 %0, 1, 0, p;\n}" : "=r"(ok) : "r"(a), "r"(ph) : "memory");
  return ok != 0;
}
constexpr uint32_t SPIN_LIMIT = 1u << 20;
__device__ __forceinline__ void mbar_wait(uint32_t a, uint32_t ph) {
  if (mbar_try(a, ph)) return;
  uint32_t it = 0;
  while (!mbar_try(a, ph)) { if (++it > SPIN_LIMIT) break; }
}
__device__ __forceinline__ unsigned ld_acquire(const unsigned* p) {
  unsigned v; asm volatile("ld.acquire.gpu.global.u32 %0, [%1];" : "=r"(v) : "l"(p) : "memory"); return v;
}
__device__ __forceinline__ unsigned ld_relaxed(const unsigned* p) {
  unsigned v; asm volatile("ld.relaxed.gpu.global.u32 %0, [%1];" : "=r"(v) : "l"(p) : "memory"); return v;
}
__device__ __forceinline__ void wait_count(const unsigned* p, unsigned target) {
  uint32_t it = 0;
  while ((int)(ld_acquire(p) - target) < 0) { if (++it > SPIN_LIMIT) break; }
}
__device__ __forceinline__ void red_release_add(unsigned* p, unsigned v) {
  asm volatile("red.release.gpu.global.add.u32 [%0], %1;" ::"l"(p), "r"(v) : "memory");
}
__device__ __forceinline__ void st_release(unsigned* p, unsigned v) {
  asm volatile("st.release.gpu.global.u32 [%0], %1;" ::"l"(p), "r"(v) : "memory");
}
__device__ __forceinline__ bool elect_one() {
  uint32_t p;
  asm volatile("{\n.reg .pred P;\nelect.sync _|P, 0xffffffff;\nselp.u32 %0, 1, 0, P;\n}" : "=r"(p));
  return p != 0;
}
__device__ __forceinline__ void bar_sync(int id, int n) { asm volatile("bar.sync %0, %1;" ::"r"(id), "r"(n) : "memory"); }
__device__ __forceinline__ void fence_async_smem() { asm volatile("fence.proxy.async.shared::cta;" ::: "memory"); }
__device__ __forceinline__ void fence_async_global() { asm volatile("fence.proxy.async.global;" ::: "memory"); }
__device__ __forceinline__ void cluster_arrive_relaxed() { asm volatile("barrier.cluster.arrive.relaxed.aligned;" ::: "memory"); }
__device__ __forceinline__ void cluster_wait() { asm volatile("barrier.cluster.wait.acquire.aligned;" ::: "memory"); }

__device__ __forceinline__ void tma2d(uint32_t dst, const CUtensorMap* m, int c0, int c1, uint32_t bar) {
  asm volatile("cp.async.bulk.tensor.2d.shared::cluster.global.mbarrier::complete_tx::bytes [%0], [%1, {%3, %4}], [%2];"
               ::"r"(dst), "l"(m), "r"(bar), "r"(c0), "r"(c1) : "memory");
}
__device__ __forceinline__ void tma3d_mc(uint32_t dst, const CUtensorMap* m, int c0, int c1, int c2, uint32_t bar) {
  asm volatile("cp.async.bulk.tensor.3d.shared::cluster.global.mbarrier::complete_tx::bytes.multicast::cluster [%0], [%1, {%3, %4, %5}], [%2], %6;"
               ::"r"(dst), "l"(m), "r"(bar), "r"(c0), "r"(c1), "r"(c2), "h"((uint16_t)3) : "memory");
}
__device__ __forceinline__ void tma3d_prefetch(const CUtensorMap* m, int c0, int c1, int c2) {
  asm volatile("cp.async.bulk.prefetch.tensor.3d.L2.global [%0, {%1, %2, %3}];" ::"l"(m), "r"(c0), "r"(c1), "r"(c2) : "memory");
}
__device__ __forceinline__ void tma3d_store(const CUtensorMap* m, int c0, int c1, int c2, uint32_t src) {
  asm volatile("cp.async.bulk.tensor.3d.global.shared::cta.bulk_group [%0, {%2, %3, %4}], [%1];"
               ::"l"(m), "r"(src), "r"(c0), "r"(c1), "r"(c2) : "memory");
}
__device__ __forceinline__ void bulk_g2s(uint32_t dst, const void* src, uint32_t bytes, uint32_t bar) {
  asm volatile("cp.async.bulk.shared::cluster.global.mbarrier::complete_tx::bytes [%0], [%1], %2, [%3];"
               ::"r"(dst), "l"(src), "r"(bytes), "r"(bar) : "memory");
}
__device__ __forceinline__ void bulk_s2g(void* dst, uint32_t src, uint32_t bytes) {
  asm volatile("cp.async.bulk.global.shared::cta.bulk_group [%0], [%1], %2;" ::"l"(dst), "r"(src), "r"(bytes) : "memory");
}
__device__ __forceinline__ void l2_prefetch(const void* src, uint32_t bytes) {
  asm volatile("cp.async.bulk.prefetch.L2.global [%0], %1;" ::"l"(src), "r"(bytes) : "memory");
}
__device__ __forceinline__ void red_relaxed_add(unsigned* p, unsigned v) {
  asm volatile("red.relaxed.gpu.global.add.u32 [%0], %1;" ::"l"(p), "r"(v) : "memory");
}
__device__ __forceinline__ void bulk_commit() { asm volatile("cp.async.bulk.commit_group;" ::: "memory"); }
__device__ __forceinline__ void bulk_wait_read0() { asm volatile("cp.async.bulk.wait_group.read 0;" ::: "memory"); }
__device__ __forceinline__ void bulk_wait0() { asm volatile("cp.async.bulk.wait_group 0;" ::: "memory"); }
__device__ __forceinline__ void prefetch_tmap(const CUtensorMap* m) { asm volatile("prefetch.tensormap [%0];" ::"l"(m) : "memory"); }

__device__ __forceinline__ void wg_fence() { asm volatile("wgmma.fence.sync.aligned;" ::: "memory"); }
__device__ __forceinline__ void wg_commit() { asm volatile("wgmma.commit_group.sync.aligned;" ::: "memory"); }
template <int N> __device__ __forceinline__ void wg_wait() { asm volatile("wgmma.wait_group.sync.aligned %0;" ::"n"(N) : "memory"); }
__device__ __forceinline__ uint64_t make_desc(uint32_t addr, uint32_t lbo, uint32_t sbo) {
  return (uint64_t)((addr & 0x3FFFF) >> 4) | ((uint64_t)(lbo >> 4) << 16) | ((uint64_t)(sbo >> 4) << 32) | (1ull << 62);
}
__device__ __forceinline__ void ldsm_x4(uint32_t (&r)[4], uint32_t a) {
  asm volatile("ldmatrix.sync.aligned.m8n8.x4.shared.b16 {%0,%1,%2,%3}, [%4];" : "=r"(r[0]), "=r"(r[1]), "=r"(r[2]), "=r"(r[3]) : "r"(a) : "memory");
}
__device__ __forceinline__ void ldsm_x4(uint32_t& r0, uint32_t& r1, uint32_t& r2, uint32_t& r3, uint32_t a) {
  asm volatile("ldmatrix.sync.aligned.m8n8.x4.shared.b16 {%0,%1,%2,%3}, [%4];" : "=r"(r0), "=r"(r1), "=r"(r2), "=r"(r3) : "r"(a) : "memory");
}
__device__ __forceinline__ void ldsm_x4_t(uint32_t& r0, uint32_t& r1, uint32_t& r2, uint32_t& r3, uint32_t a) {
  asm volatile("ldmatrix.sync.aligned.m8n8.x4.trans.shared.b16 {%0,%1,%2,%3}, [%4];" : "=r"(r0), "=r"(r1), "=r"(r2), "=r"(r3) : "r"(a) : "memory");
}
__device__ __forceinline__ void ldsm_x2(uint32_t& r0, uint32_t& r1, uint32_t a) {
  asm volatile("ldmatrix.sync.aligned.m8n8.x2.shared.b16 {%0,%1}, [%2];" : "=r"(r0), "=r"(r1) : "r"(a) : "memory");
}
__device__ __forceinline__ void ldsm_x2_t(uint32_t& r0, uint32_t& r1, uint32_t a) {
  asm volatile("ldmatrix.sync.aligned.m8n8.x2.trans.shared.b16 {%0,%1}, [%2];" : "=r"(r0), "=r"(r1) : "r"(a) : "memory");
}
__device__ __forceinline__ void stsm_x4(uint32_t a, uint32_t r0, uint32_t r1, uint32_t r2, uint32_t r3) {
  asm volatile("stmatrix.sync.aligned.m8n8.x4.shared.b16 [%0], {%1,%2,%3,%4};" ::"r"(a), "r"(r0), "r"(r1), "r"(r2), "r"(r3) : "memory");
}
__device__ __forceinline__ void stsm_x2(uint32_t a, uint32_t r0, uint32_t r1) {
  asm volatile("stmatrix.sync.aligned.m8n8.x2.shared.b16 [%0], {%1,%2};" ::"r"(a), "r"(r0), "r"(r1) : "memory");
}
__device__ __forceinline__ void stsm_x4_t(uint32_t a, uint32_t r0, uint32_t r1, uint32_t r2, uint32_t r3) {
  asm volatile("stmatrix.sync.aligned.m8n8.x4.trans.shared.b16 [%0], {%1,%2,%3,%4};" ::"r"(a), "r"(r0), "r"(r1), "r"(r2), "r"(r3) : "memory");
}
__device__ __forceinline__ void hmma(float (&c)[4], uint32_t a0, uint32_t a1, uint32_t a2, uint32_t a3, uint32_t b0, uint32_t b1) {
  asm volatile("mma.sync.aligned.m16n8k16.row.col.f32.bf16.bf16.f32 {%0,%1,%2,%3}, {%4,%5,%6,%7}, {%8,%9}, {%0,%1,%2,%3};"
               : "+f"(c[0]), "+f"(c[1]), "+f"(c[2]), "+f"(c[3]) : "r"(a0), "r"(a1), "r"(a2), "r"(a3), "r"(b0), "r"(b1));
}
__device__ __forceinline__ uint32_t lds32(uint32_t a) { uint32_t v; asm volatile("ld.shared.u32 %0, [%1];" : "=r"(v) : "r"(a) : "memory"); return v; }
__device__ __forceinline__ uint32_t lds32v(uint32_t a) { uint32_t v; asm volatile("ld.volatile.shared.u32 %0, [%1];" : "=r"(v) : "r"(a) : "memory"); return v; }
__device__ __forceinline__ void ld_relaxed_v4(uint4& v, const uint4* p) {
  asm volatile("ld.relaxed.gpu.global.v4.u32 {%0,%1,%2,%3}, [%4];" : "=r"(v.x), "=r"(v.y), "=r"(v.z), "=r"(v.w) : "l"(p) : "memory");
}
__device__ __forceinline__ uint4 lds128(uint32_t a) {
  uint4 v; asm volatile("ld.shared.v4.u32 {%0,%1,%2,%3}, [%4];" : "=r"(v.x), "=r"(v.y), "=r"(v.z), "=r"(v.w) : "r"(a) : "memory"); return v;
}
__device__ __forceinline__ void sts128(uint32_t a, uint4 v) {
  asm volatile("st.shared.v4.u32 [%0], {%1,%2,%3,%4};" ::"r"(a), "r"(v.x), "r"(v.y), "r"(v.z), "r"(v.w) : "memory");
}
__device__ __forceinline__ void sts64(uint32_t a, uint32_t x, uint32_t y) { asm volatile("st.shared.v2.u32 [%0], {%1,%2};" ::"r"(a), "r"(x), "r"(y) : "memory"); }
__device__ __forceinline__ uint32_t bmul2(uint32_t a, uint32_t b) { uint32_t d; asm("mul.rn.bf16x2 %0, %1, %2;" : "=r"(d) : "r"(a), "r"(b)); return d; }
__device__ __forceinline__ uint32_t badd2(uint32_t a, uint32_t b) { uint32_t d; asm("add.rn.bf16x2 %0, %1, %2;" : "=r"(d) : "r"(a), "r"(b)); return d; }
__device__ __forceinline__ uint32_t bsub2(uint32_t a, uint32_t b) { uint32_t d; asm("sub.rn.bf16x2 %0, %1, %2;" : "=r"(d) : "r"(a), "r"(b)); return d; }
__device__ __forceinline__ uint32_t bfma2(uint32_t a, uint32_t b, uint32_t c) { uint32_t d; asm("fma.rn.bf16x2 %0, %1, %2, %3;" : "=r"(d) : "r"(a), "r"(b), "r"(c)); return d; }
__device__ __forceinline__ uint32_t bmax2(uint32_t a, uint32_t b) { uint32_t d; asm("max.bf16x2 %0, %1, %2;" : "=r"(d) : "r"(a), "r"(b)); return d; }
__device__ __forceinline__ uint32_t pack_bf16(float lo, float hi) { uint32_t d; asm("cvt.rn.bf16x2.f32 %0, %1, %2;" : "=r"(d) : "f"(hi), "f"(lo)); return d; }
__device__ __forceinline__ float bf16_round(float x) { return __bfloat162float(__float2bfloat16_rn(x)); }
__device__ __forceinline__ float sqrt_approx(float x) { float y; asm("sqrt.approx.f32 %0, %1;" : "=f"(y) : "f"(x)); return y; }
__device__ __forceinline__ float rcp_approx(float x) { float y; asm("rcp.approx.f32 %0, %1;" : "=f"(y) : "f"(x)); return y; }
__device__ __forceinline__ uint32_t dup_bf16(float x) { return pack_bf16(x, x); }

__device__ __forceinline__ void wgmma_rs_n128(float (&d)[64], const uint32_t (&a)[4], uint64_t db, int sc) {
  asm volatile("{\n.reg .pred p;\nsetp.ne.b32 p, %69, 0;\n"
    "wgmma.mma_async.sync.aligned.m64n128k16.f32.bf16.bf16 "
    "{%0,%1,%2,%3,%4,%5,%6,%7,%8,%9,%10,%11,%12,%13,%14,%15,%16,%17,%18,%19,%20,%21,%22,%23,%24,%25,%26,%27,%28,%29,%30,%31,%32,%33,%34,%35,%36,%37,%38,%39,%40,%41,%42,%43,%44,%45,%46,%47,%48,%49,%50,%51,%52,%53,%54,%55,%56,%57,%58,%59,%60,%61,%62,%63}, "
    "{%64,%65,%66,%67}, %68, p, 1, 1, 1;\n}\n"
    : "+f"(d[0]),"+f"(d[1]),"+f"(d[2]),"+f"(d[3]),"+f"(d[4]),"+f"(d[5]),"+f"(d[6]),"+f"(d[7]),"+f"(d[8]),"+f"(d[9]),"+f"(d[10]),"+f"(d[11]),"+f"(d[12]),"+f"(d[13]),"+f"(d[14]),"+f"(d[15]),"+f"(d[16]),"+f"(d[17]),"+f"(d[18]),"+f"(d[19]),"+f"(d[20]),"+f"(d[21]),"+f"(d[22]),"+f"(d[23]),"+f"(d[24]),"+f"(d[25]),"+f"(d[26]),"+f"(d[27]),"+f"(d[28]),"+f"(d[29]),"+f"(d[30]),"+f"(d[31]),"+f"(d[32]),"+f"(d[33]),"+f"(d[34]),"+f"(d[35]),"+f"(d[36]),"+f"(d[37]),"+f"(d[38]),"+f"(d[39]),"+f"(d[40]),"+f"(d[41]),"+f"(d[42]),"+f"(d[43]),"+f"(d[44]),"+f"(d[45]),"+f"(d[46]),"+f"(d[47]),"+f"(d[48]),"+f"(d[49]),"+f"(d[50]),"+f"(d[51]),"+f"(d[52]),"+f"(d[53]),"+f"(d[54]),"+f"(d[55]),"+f"(d[56]),"+f"(d[57]),"+f"(d[58]),"+f"(d[59]),"+f"(d[60]),"+f"(d[61]),"+f"(d[62]),"+f"(d[63])
    : "r"(a[0]),"r"(a[1]),"r"(a[2]),"r"(a[3]),"l"(db),"r"(sc));
}
__device__ __forceinline__ void wgmma_rs_n32(float (&d)[16], const uint32_t (&a)[4], uint64_t db, int sc) {
  asm volatile("{\n.reg .pred p;\nsetp.ne.b32 p, %21, 0;\n"
    "wgmma.mma_async.sync.aligned.m64n32k16.f32.bf16.bf16 "
    "{%0,%1,%2,%3,%4,%5,%6,%7,%8,%9,%10,%11,%12,%13,%14,%15}, "
    "{%16,%17,%18,%19}, %20, p, 1, 1, 1;\n}\n"
    : "+f"(d[0]),"+f"(d[1]),"+f"(d[2]),"+f"(d[3]),"+f"(d[4]),"+f"(d[5]),"+f"(d[6]),"+f"(d[7]),"+f"(d[8]),"+f"(d[9]),"+f"(d[10]),"+f"(d[11]),"+f"(d[12]),"+f"(d[13]),"+f"(d[14]),"+f"(d[15])
    : "r"(a[0]),"r"(a[1]),"r"(a[2]),"r"(a[3]),"l"(db),"r"(sc));
}
__device__ __forceinline__ void wgmma_ss_n112(float (&d)[56], uint64_t da, uint64_t db, int sc) {
  asm volatile("{\n.reg .pred p;\nsetp.ne.b32 p, %58, 0;\n"
    "wgmma.mma_async.sync.aligned.m64n112k16.f32.bf16.bf16 "
    "{%0,%1,%2,%3,%4,%5,%6,%7,%8,%9,%10,%11,%12,%13,%14,%15,%16,%17,%18,%19,%20,%21,%22,%23,%24,%25,%26,%27,%28,%29,%30,%31,%32,%33,%34,%35,%36,%37,%38,%39,%40,%41,%42,%43,%44,%45,%46,%47,%48,%49,%50,%51,%52,%53,%54,%55}, "
    "%56, %57, p, 1, 1, 0, 1;\n}\n"
    : "+f"(d[0]),"+f"(d[1]),"+f"(d[2]),"+f"(d[3]),"+f"(d[4]),"+f"(d[5]),"+f"(d[6]),"+f"(d[7]),"+f"(d[8]),"+f"(d[9]),"+f"(d[10]),"+f"(d[11]),"+f"(d[12]),"+f"(d[13]),"+f"(d[14]),"+f"(d[15]),"+f"(d[16]),"+f"(d[17]),"+f"(d[18]),"+f"(d[19]),"+f"(d[20]),"+f"(d[21]),"+f"(d[22]),"+f"(d[23]),"+f"(d[24]),"+f"(d[25]),"+f"(d[26]),"+f"(d[27]),"+f"(d[28]),"+f"(d[29]),"+f"(d[30]),"+f"(d[31]),"+f"(d[32]),"+f"(d[33]),"+f"(d[34]),"+f"(d[35]),"+f"(d[36]),"+f"(d[37]),"+f"(d[38]),"+f"(d[39]),"+f"(d[40]),"+f"(d[41]),"+f"(d[42]),"+f"(d[43]),"+f"(d[44]),"+f"(d[45]),"+f"(d[46]),"+f"(d[47]),"+f"(d[48]),"+f"(d[49]),"+f"(d[50]),"+f"(d[51]),"+f"(d[52]),"+f"(d[53]),"+f"(d[54]),"+f"(d[55])
    : "l"(da),"l"(db),"r"(sc));
}

#define PROF(slot) do {} while (0)
#define PROFG(slot) do {} while (0)
#define PROF2(slot) do {} while (0)

#define TOUCH_PART 0
#define SCHED_NR0 2
#define SCHED_NS0 4
#define SCHED_NR1 1
#define SCHED_NS1 5
#define SYNC_CHUNK 1
#define XST_MODE 1
#define XST "st.global.cg.v4.u32"
#define MAP_MODE 1
#define SEND_LEAD_CUT 0
#define PF_W0 0
__device__ __forceinline__ int wcol(int p, int f) { return (f & 1) ? (p < 3 ? 32 + 64 * p : -32) : 64 * p; }

struct Ring {
  uint32_t slot, phase;
  __device__ __forceinline__ void next() { if (++slot == NSLOT) { slot = 0; phase ^= 1; } }
};

__device__ __forceinline__ void release_slot(uint32_t sb, uint32_t slot, bool leader) {
  if (leader) {
    const uint32_t a = sb + OFF_BAR + 8 * (B_EMPTY + slot);
    mbar_arrive_cta(a, 0);
    mbar_arrive_cta(a, 1);
  }
}

template <int MODE>
__device__ __forceinline__ void gemm1_pass(float (&acc)[64], float (&ag)[16], float (&au)[16], uint32_t (&xa)[28][4],
                                           const uint32_t (&m2)[2], const uint32_t (&rh2)[2], const uint32_t (&rl2)[2],
                                           Ring& rg, uint32_t sb, bool leader, int cw, int pslot, uint32_t hoff) {
  uint32_t prev = 0;
#pragma unroll
  for (int s = 0; s < 4; ++s) {
    if (MODE == 0) {
#pragma unroll
      for (int kk = 7 * s; kk < 7 * s + 7; ++kk) {
#pragma unroll
        for (int i = 0; i < 4; ++i) {
          const uint32_t d = bsub2(xa[kk][i], m2[i & 1]);
          xa[kk][i] = bfma2(d, rh2[i & 1], bmul2(d, rl2[i & 1]));
        }
      }
      if (s == 0 && cw == 1) bar_sync(3, 256);
    }
    if (pslot >= 0) PROF2(pslot + 2 * s);
    mbar_wait(sb + OFF_BAR + 8 * (B_FULL + rg.slot), rg.phase);
    if (pslot >= 0) PROF2(pslot + 2 * s + 1);
    const uint32_t base = sb + OFF_RING + rg.slot * SLOT_BYTES;
    const uint64_t db = make_desc(base + (MODE == 2 ? hoff : 0u), 14336, 1024);
    wg_fence();
#pragma unroll
    for (int kk = 0; kk < 7; ++kk) {
      const int sc = (s == 0 && kk == 0) ? 0 : 1;
      if (MODE != 2) {
        wgmma_rs_n128(acc, xa[7 * s + kk], db + kk * 128, sc);
      } else {
        wgmma_rs_n32(ag, xa[7 * s + kk], db + kk * 128, sc);
        wgmma_rs_n32(au, xa[7 * s + kk], db + kk * 128 + (14336 >> 4), sc);
      }
    }
    wg_commit();
    if (MODE == 0 && s == 0 && cw == 0) asm volatile("bar.arrive 3, 256;" ::: "memory");
    if (s > 0) { wg_wait<1>(); release_slot(sb, prev, leader); }
    prev = rg.slot;
    rg.next();
  }
  wg_wait<0>();
  release_slot(sb, prev, leader);
}

template <int NG>
__device__ __forceinline__ void gemm1_stage_h(const float* gate, const float* up, uint32_t saddr, uint32_t srow, int lane, uint32_t choff) {
#pragma unroll
  for (int j = 0; j < NG; j += 2) {
    uint32_t h[4];
#pragma unroll
    for (int i = 0; i < 4; ++i) {
      const int o = 4 * (j + (i >> 1)) + 2 * (i & 1);
      h[i] = bmul2(bmax2(pack_bf16(gate[o], gate[o + 1]), 0u), pack_bf16(up[o], up[o + 1]));
    }
    stsm_x4(saddr + (((choff + j + (lane >> 4)) ^ (srow & 7)) << 4), h[0], h[1], h[2], h[3]);
  }
  fence_async_smem();
}

__device__ __forceinline__ void kv_prepass(uint32_t ka, uint32_t va, const uint4 w0, int b, int cp) {
  const uint32_t t0 = __byte_perm(w0.x, w0.z, 0x5410), t1 = __byte_perm(w0.x, w0.z, 0x7632);
  const uint32_t t2 = __byte_perm(w0.y, w0.w, 0x5410), t3 = __byte_perm(w0.y, w0.w, 0x7632);
  uint32_t kr[19], vr[16];
#pragma unroll
  for (int i = 0; i < 19; ++i) kr[i] = lds32(ka + cp * 4 + i * 896);
#pragma unroll
  for (int i = 0; i < 16; ++i) vr[i] = lds32(va + cp * 4 + (i >> 2) * SLOT_BYTES + (i & 3) * 896);
  uint32_t o0[8], o1[8];
#pragma unroll
  for (int i = 0; i < 16; i += 2) {
    uint32_t kv[2];
#pragma unroll
    for (int e = 0; e < 2; ++e) {
      uint32_t a = bmul2(kr[i + e], t3);
      a = badd2(a, bmul2(kr[i + e + 1], t2));
      a = badd2(a, bmul2(kr[i + e + 2], t1));
      a = badd2(a, bmul2(kr[i + e + 3], t0));
      kv[e] = bmul2(a, vr[i + e]);
    }
    o0[7 - (i >> 1)] = __byte_perm(kv[1], kv[0], 0x5410);
    o1[7 - (i >> 1)] = __byte_perm(kv[1], kv[0], 0x7632);
  }
  const int sw = (b >> 2) & 1;
  uint4* d0 = reinterpret_cast<uint4*>(g_kvT + (size_t)(2 * cp) * S_LEN + b * 16);
  uint4* d1 = reinterpret_cast<uint4*>(g_kvT + (size_t)(2 * cp + 1) * S_LEN + b * 16);
  d0[sw]     = make_uint4(o0[0], o0[1], o0[2], o0[3]);
  d0[sw ^ 1] = make_uint4(o0[4], o0[5], o0[6], o0[7]);
  d1[sw]     = make_uint4(o1[0], o1[1], o1[2], o1[3]);
  d1[sw ^ 1] = make_uint4(o1[4], o1[5], o1[6], o1[7]);
}

__global__ void __cluster_dims__(2, 1, 1) __launch_bounds__(NTHREADS, 1)
fused_h3_mlp_kernel(const __grid_constant__ Params P) {
  extern __shared__ __align__(1024) uint8_t smem[];
  const uint32_t sb = smem_u32(smem);
  const int tid = threadIdx.x, warp = tid >> 5, lane = tid & 31;
  const int b = blockIdx.x;
  const int rank = b & 1;
  const int pr = b >> 1, f = pr >> 3, mt = (pr & 7) * 2 + rank;
  const int partner = b ^ 64;
  const int jq = f & 3, kap = f >> 2;
  const uint32_t bar = sb + OFF_BAR;
  const bool has_conv = b < CONV_CTAS;

  if (warp == 0) { PROF(0); PROFG(60); }
  if (tid == 0) {
    for (int i = 0; i < 7; ++i) mbar_init(bar + 8 * (B_XFULL + i), 1);
    fence_async_smem();
#pragma unroll
    for (int cb = 0; cb < 7; ++cb) {
      const uint32_t dst = cb < 4 ? OFF_RING + 3 * SLOT_BYTES + cb * 16384 : (cb == 4 ? OFF_HST : OFF_C + (cb - 5) * 16384);
      mbar_expect_tx(bar + 8 * (B_XFULL + cb), 16384);
      tma2d(sb + dst, &P.tm_x, cb * 64, mt * 128, bar + 8 * (B_XFULL + cb));
    }
    PROF(6);
  } else if (tid == 32) {
    for (int i = 0; i < NSLOT; ++i) { mbar_init(bar + 8 * (B_FULL + i), 1); mbar_init(bar + 8 * (B_EMPTY + i), 4); }
    mbar_init(bar + 8 * B_HRAW, 1);
    mbar_init(bar + 8 * B_KVFULL, 1);
    mbar_init(bar + 8 * B_CONVRDY, 97);
    mbar_init(bar + 8 * B_EPIFULL, 1);
    mbar_init(bar + 8 * B_CONVDONE, 8);
    mbar_init(bar + 8 * B_HSTF, 4); mbar_init(bar + 8 * (B_HSTF + 1), 4);
    mbar_init(bar + 8 * B_HSTE, 1); mbar_init(bar + 8 * (B_HSTE + 1), 1);
    mbar_init(bar + 8 * B_YFULL, 8);
    asm volatile("fence.mbarrier_init.release.cluster;" ::: "memory");
    fence_async_smem();
  } else if (tid == 64) {
    prefetch_tmap(&P.tm_wg); prefetch_tmap(&P.tm_wu); prefetch_tmap(&P.tm_hs); prefetch_tmap(&P.tm_hh); prefetch_tmap(&P.tm_hl);
    prefetch_tmap(&P.tm_wd); prefetch_tmap(&P.tm_xe); prefetch_tmap(&P.tm_y); prefetch_tmap(&P.tm_out);
  } else if (tid == 96) {
  }
  __syncthreads();
  cluster_arrive_relaxed();
  cluster_wait();
  if (warp == 0) PROF(12);

  if (warp < 4) {
    asm volatile("setmaxnreg.dec.sync.aligned.u32 88;");
    const unsigned epoch = ld_relaxed(&g_sync.epoch);
    if (warp == 0) {
      uint32_t slot = 0, use = 0;
#pragma unroll 1
      for (int n = 0; n < 30; ++n) {
        if (slot >= 3) mbar_wait(bar + 8 * (B_EMPTY + slot), use & 1);
        else if (use > 0) mbar_wait(bar + 8 * (B_EMPTY + slot), (use - 1) & 1);
        const uint32_t fb = bar + 8 * (B_FULL + slot);
        const uint32_t dst = sb + OFF_RING + slot * SLOT_BYTES;
        if (n < 16) {
          if (elect_one()) {
            mbar_expect_tx(fb, 28672);
            tma3d_mc(dst + rank * 14336, rank ? &P.tm_wu : &P.tm_wg, wcol(n >> 2, f), f, (n & 3) * 112, fb);
            if (n == 3) {
              const uint32_t kb = bar + 8 * B_KVFULL;
              const int r0 = b * 16;
              if (b == 0) {
                mbar_expect_tx(kb, 16 * 896 * 2);
                bulk_g2s(sb + OFF_KST + 3 * 896, P.k, 16 * 896, kb);
              } else {
                mbar_expect_tx(kb, 19 * 896 + 16 * 896);
                bulk_g2s(sb + OFF_KST, P.k + (size_t)(r0 - 3) * D_DIM, 19 * 896, kb);
              }
#pragma unroll
              for (int c = 0; c < 4; ++c)
                bulk_g2s(sb + OFF_RING + c * SLOT_BYTES + OFF_VTAIL, P.v + (size_t)(r0 + 4 * c) * D_DIM, 4 * 896, kb);
              if (has_conv) {
                const uint32_t hb = bar + 8 * B_HRAW;
                mbar_expect_tx(hb, 4 * 4096);
#pragma unroll
                for (int c = 0; c < 4; ++c)
                  bulk_g2s(sb + OFF_HC + c * HC_BYTES + HC_COPY0 + 32, P.ssm_k + (size_t)(4 * b + c) * S_LEN, 4096, hb);
              }
            }
          }
        } else {
          const int t = n - 16;
          const int kt = (int)((0xA3D962C851B740ull >> (4 * t)) & 15);
          const int k0 = kap * 896 + kt * 64;
          if (elect_one()) {
            mbar_expect_tx(fb, 32768);
            tma3d_mc(dst + 16384 + rank * 8192, &P.tm_wd, rank * 64, jq, k0, fb);
          }
          if (t == 0 || t == 8) {
            wait_count(&g_sync.cnt_h[(mt * 2 + kap) * 32 + (t ? 16 : 0)], 4u * (epoch + 1));
            fence_async_global();
            if (t == 0) PROF(3);
          }
          __syncwarp();
          if (elect_one()) tma2d(dst, &P.tm_hl, k0, mt * 128, fb);
        }
        __syncwarp();
        PROF2(n);
        if (n == 2) PROF(1);
        if (n == 15) PROF(2);
        if (++slot == NSLOT) { slot = 0; ++use; }
      }
      PROF(4);
    } else {
      if (warp == 1) {
        if (has_conv) {
          mbar_wait(bar + 8 * B_HRAW, 0);
#pragma unroll 1
          for (int c = 0; c < 4; ++c) {
            const uint32_t hb = sb + OFF_HC + c * HC_BYTES;
            uint4 v[8];
#pragma unroll
            for (int i = 0; i < 8; ++i) v[i] = lds128(hb + HC_COPY0 + 32 + (i * 32 + lane) * 16);
#pragma unroll
            for (int i = 0; i < 8; ++i) {
              uint32_t nx = __shfl_down_sync(0xffffffffu, v[i].x, 1);
              const uint32_t first_next = __shfl_sync(0xffffffffu, v[i < 7 ? i + 1 : 7].x, 0);
              if (lane == 31) nx = i < 7 ? first_next : 0u;
              sts128(hb + 32 + (i * 32 + lane) * 16, make_uint4(__byte_perm(v[i].x, v[i].y, 0x5432), __byte_perm(v[i].y, v[i].z, 0x5432),
                                                                 __byte_perm(v[i].z, v[i].w, 0x5432), __byte_perm(v[i].w, nx, 0x5432)));
            }
            if (lane == 0) {
              sts128(hb + HC_COPY0, make_uint4(0, 0, 0, 0));
              sts128(hb + HC_COPY0 + 16, make_uint4(0, 0, 0, 0));
              sts128(hb, make_uint4(0, 0, 0, 0));
              sts128(hb + 16, make_uint4(0, 0, 0, v[0].x << 16));
            }
          }
          mbar_arrive(bar + 8 * B_CONVRDY);
        }
        PROF(8);
        mbar_wait(bar + 8 * B_HSTE, 0);
        mbar_wait(bar + 8 * (B_HSTE + 1), 0);
        if (lane == 0) red_relaxed_add(&g_sync.cnt_h[(mt * 2 + kap) * 32], 1);
        __syncwarp();
#pragma unroll 1
        for (int w = 0; w < 2; ++w) {
          mbar_wait(bar + 8 * (B_HSTF + w), 0);
          if (lane == 0) { tma3d_store(&P.tm_hh, 0, 7 * f + ((f & 1) ? 0 : 6), mt * 128 + w * 64, sb + OFF_HST + w * 8192); bulk_commit(); }
          __syncwarp();
        }
        const uint32_t eb = bar + 8 * B_EPIFULL;
        if (lane == 0) {
          bulk_wait0();
          red_relaxed_add(&g_sync.cnt_h[(mt * 2 + kap) * 32 + 16], 1);
          mbar_expect_tx(eb, 16384 + 14336);
          tma2d(sb + OFF_HST, &P.tm_xe, jq * 112, mt * 128 + kap * 64, eb);
          tma2d(sb + OFF_HST + 8192, &P.tm_xe, jq * 112 + 64, mt * 128 + kap * 64, eb);
        }
        __syncwarp();
        PROF(9);
        if (has_conv) {
          mbar_wait(bar + 8 * B_YFULL, 0);
          PROF(51);
          if (lane == 0) {
#pragma unroll
            for (int i = 0; i < 8; ++i)
              bulk_s2g(g_y2T + (size_t)(4 * b + (i >> 1)) * S_LEN + (i & 1) * 1024,
                       sb + OFF_HC + (i >> 1) * HC_BYTES + (i & 1) * 4096, 2048);
            bulk_commit();
            bulk_wait0();
            red_relaxed_add(&g_sync.cnt_y[(b / 28) * 32], 1);
          }
          __syncwarp();
        }
        PROF(10);
        mbar_wait(bar + 8 * B_CONVDONE, 0);
        wait_count(&g_sync.cnt_y[jq * 32], 28u * (epoch + 1));
        fence_async_global();
        __syncwarp();
        if (lane == 0) tma2d(sb + OFF_C, &P.tm_y, mt * 128 + kap * 64, jq * 112, eb);
        PROF(11);
      } else {
        const int at = tid - 64;
        uint4 wsh[4];
#pragma unroll
        for (int i = 0; i < 4; ++i) {
          const int cp = at + 64 * i;
          wsh[i] = cp < 224 ? __ldg(reinterpret_cast<const uint4*>(P.shift_k) + cp) : make_uint4(0, 0, 0, 0);
        }
        mbar_wait(bar + 8 * B_KVFULL, 0);
        if (warp == 3) PROF(7);
        if (b == 0) {
          for (int i = at; i < 3 * 896 / 16; i += 64) sts128(sb + OFF_KST + i * 16, make_uint4(0, 0, 0, 0));
          bar_sync(4, 64);
        }
#pragma unroll
        for (int i = 0; i < 4; ++i) {
          const int cp = at + 64 * i;
          if (cp < 224) kv_prepass(sb + OFF_KST, sb + OFF_RING + OFF_VTAIL, wsh[i], b, cp);
        }
        bar_sync(4, 64);
        if (warp == 2) PROF(14);
        if (at == 32) red_release_add(&g_sync.cnt_kv, 1);
        if (has_conv) {
          sts128(sb + OFF_U + (at >> 4) * U_BYTES + (at & 15) * 16, make_uint4(0, 0, 0, 0));
          if (warp == 2) {
            wait_count(&g_sync.cnt_kv, (unsigned)NCTA * (epoch + 1));
            fence_async_global();
            __syncwarp();
            if (lane == 0) {
              const uint32_t cb = bar + 8 * B_CONVRDY;
              mbar_expect_tx(cb, 4 * 4096);
#pragma unroll
              for (int c = 0; c < 4; ++c) bulk_g2s(sb + OFF_U + c * U_BYTES + 256, g_kvT + (size_t)(4 * b + c) * S_LEN, 4096, cb);
            }
            PROF(5);
          }
          mbar_arrive(bar + 8 * B_CONVRDY);
        }
      }
    }
    cluster_arrive_relaxed();
    cluster_wait();
  } else {
    asm volatile("setmaxnreg.inc.sync.aligned.u32 208;");
    const int cw = (warp >> 2) - 1, wq = warp & 3;
    const int g = lane >> 2, t = lane & 3;
    const bool leader = (tid & 127) == 0;
    const int pb = (warp & 3) == 0 ? (cw == 0 ? 16 : 32) : -1;
    (void)pb;
    const unsigned epoch = ld_relaxed(&g_sync.epoch);
    uint32_t dv = 0;
    if (has_conv) dv = __bfloat16_as_ushort(__ldg(P.ssm_D + 4 * b + ((warp - 4) >> 1)));

    uint32_t xa[28][4];
    uint32_t m2[2], rh2[2], rl2[2];
    {
      float cs[2][4] = {}, q0[2][4] = {}, q1[2][4] = {};
      const uint32_t lrow = cw * 64 + wq * 16 + (lane & 7) + ((lane >> 3) & 1) * 8;
      const uint32_t lch = lane >> 4;
#pragma unroll
      for (int cb = 0; cb < 7; ++cb) {
        mbar_wait(bar + 8 * (B_XFULL + cb), 0);
        const uint32_t boxo = cb < 4 ? OFF_RING + 3 * SLOT_BYTES + cb * 16384 : (cb == 4 ? OFF_HST : OFF_C + (cb - 5) * 16384);
        const uint32_t base = sb + boxo + lrow * 128;
#pragma unroll
        for (int c = 0; c < 4; ++c) {
          const int kk = 4 * cb + c;
          ldsm_x4(xa[kk], base + (((2 * c + lch) ^ (lrow & 7)) << 4));
          hmma(cs[kk & 1], xa[kk][0], xa[kk][1], xa[kk][2], xa[kk][3], 0x3F803F80u, 0x3F803F80u);
          hmma(q0[kk & 1], xa[kk][0], xa[kk][1], xa[kk][2], xa[kk][3], xa[kk][0], xa[kk][2]);
          hmma(q1[kk & 1], xa[kk][0], xa[kk][1], xa[kk][2], xa[kk][3], xa[kk][1], xa[kk][3]);
        }
      }
      if (pb >= 0) PROF(pb + 0);
      bar_sync(1 + cw, 128);
      release_slot(sb, 3, leader);
      release_slot(sb, 4, leader);
      const int src = (lane & ~3) | (g >> 1);
      const float sqa = __shfl_sync(0xffffffffu, (g & 1) ? q0[0][1] + q0[1][1] : q0[0][0] + q0[1][0], src);
      const float sqb = __shfl_sync(0xffffffffu, (g & 1) ? q1[0][3] + q1[1][3] : q1[0][2] + q1[1][2], src);
#pragma unroll
      for (int r = 0; r < 2; ++r) {
        const float sum = cs[0][2 * r] + cs[1][2 * r];
        const float sq = r ? sqb : sqa;
        const float mean = sum * (1.0f / D_DIM);
        const float var = fmaxf(sq * (1.0f / D_DIM) - mean * mean, 0.0f);
        const float den = bf16_round(sqrt_approx(bf16_round(bf16_round(var) + 1e-5f)));
        const float rinv = rcp_approx(den);
        const float rh = bf16_round(rinv);
        m2[r] = dup_bf16(mean); rh2[r] = dup_bf16(rh); rl2[r] = dup_bf16(rinv - rh);
        if (t == 0) sts64(sb + OFF_STAT + (cw * 64 + wq * 16 + g + 8 * r) * 8, (m2[r] & 0xffffu) | (rh2[r] << 16), rl2[r] & 0xffffu);
      }
    }
    if (pb >= 0) PROF(pb + 1);

    Ring rg{0, 0};
    {
      const uint32_t srow = wq * 16 + (lane & 7) + ((lane >> 3) & 1) * 8;
      const uint32_t saddr = sb + OFF_HST + cw * 8192 + srow * 128;
      float acc[64], ag[16], au[16];
      const uint32_t stg = sb + OFF_HST + cw * 8192;
      gemm1_pass<0>(acc, ag, au, xa, m2, rh2, rl2, rg, sb, leader, cw, wq == 0 ? 32 + cw * 32 : -1000, 0);
      gemm1_stage_h<8>(acc, acc + 32, saddr, srow, lane, 0);
      bar_sync(1 + cw, 128);
      if (leader) { tma3d_store(&P.tm_hs, wcol(0, f), f, mt * 128 + cw * 64, stg); bulk_commit(); }
      if (pb >= 0) PROF(pb + 2);
#pragma unroll 1
      for (int p = 1; p < 3; ++p) {
        gemm1_pass<1>(acc, ag, au, xa, m2, rh2, rl2, rg, sb, leader, cw, wq == 0 ? 32 + cw * 32 + 8 * p : -1000, 0);
        if (leader) {
          if (p == 2) { bulk_wait0(); mbar_arrive(bar + 8 * (B_HSTE + cw)); }
          else bulk_wait_read0();
        }
        bar_sync(1 + cw, 128);
        gemm1_stage_h<8>(acc, acc + 32, saddr, srow, lane, 0);
        bar_sync(1 + cw, 128);
        if (leader) { tma3d_store(&P.tm_hs, wcol(p, f), f, mt * 128 + cw * 64, stg); bulk_commit(); }
        if (pb >= 0) PROF(pb + 2 + p);
      }
      gemm1_pass<2>(acc, ag, au, xa, m2, rh2, rl2, rg, sb, leader, cw, wq == 0 ? 32 + cw * 32 + 24 : -1000, (f & 1) * 64);
      if (leader) bulk_wait0();
      bar_sync(1 + cw, 128);
      gemm1_stage_h<4>(ag, au, saddr, srow, lane, 0);
      __syncwarp();
      if (lane == 0) mbar_arrive(bar + 8 * (B_HSTF + cw));
    }
    if (pb >= 0) PROF(pb + 5);

    const int cwarp = warp - 4, cc_ = cwarp >> 1, hh = cwarp & 1;
    const uint32_t ub = sb + OFF_U + cc_ * U_BYTES;
    const uint32_t hb = sb + OFF_HC + cc_ * HC_BYTES;
    float cacc[16][4];
#pragma unroll
    for (int i = 0; i < 16; ++i) { cacc[i][0] = cacc[i][1] = cacc[i][2] = cacc[i][3] = 0.f; }
    const uint32_t abase = hb + ((g & 1) ? HC_COPY0 + 4 * (((1 + g) >> 1) + t) : 4 * ((g >> 1) + t));
    float acc2[56];
    uint32_t dfrag = 0;
    if (has_conv) {
      const int e = 7 - g - 2 * t;
      dfrag = (e == 0) ? dv : (e == 1 ? dv << 16 : 0u);
      mbar_wait(bar + 8 * B_CONVRDY, 0);
    }
    if (pb >= 0) PROF(pb + 6);
    int r = 4 * hh, st = 0;
    uint32_t prev = 0;
#pragma unroll 1
    for (int seg = 0; seg < 3; ++seg) {
      if (has_conv) {
        const int rend = seg == 2 ? 4 * hh + 4 : r + (seg == 0 ? SCHED_NR0 : SCHED_NR1);
#pragma unroll 1
        for (; r < rend; ++r) {
          if (warp == 4) PROF2(124 + r);
          const uint32_t R = 8 + 8 * (lane >> 4) + (lane & 7) - r;
          const uint32_t baddr = ub + 32 * R + 16 * (((lane >> 3) & 1) ^ ((R >> 2) & 1));
          const uint32_t aaddr = abase + 32 * r;
          uint32_t bf[16][2];
#pragma unroll
          for (int jp = 7; jp >= 0; --jp) ldsm_x4(bf[2 * jp][0], bf[2 * jp][1], bf[2 * jp + 1][0], bf[2 * jp + 1][1], baddr + 512 * jp);
          if (r == 0) {
#pragma unroll
            for (int tau = 15; tau >= 0; --tau) hmma(cacc[tau], 0u, dfrag, dfrag, 0u, bf[tau][0], bf[tau][1]);
          }
          uint32_t aL[4], aS[4];
          aL[0] = lds32v(aaddr); aL[1] = lds32v(aaddr + 16); aL[3] = lds32v(aaddr + 32);
          aS[0] = lds32v(aaddr + 256 * 15); aS[1] = lds32v(aaddr + 256 * 15 + 16); aS[3] = lds32v(aaddr + 256 * 15 + 32);
          aL[2] = lds32v(aaddr + 16); aS[2] = lds32v(aaddr + 256 * 15 + 16);
#pragma unroll
          for (int q = 0; q < 8; ++q) {
            const int q2 = 15 - q;
            uint32_t nL[4] = {0, 0, 0, 0}, nS[4] = {0, 0, 0, 0};
            if (q < 7) {
              nL[0] = lds32v(aaddr + 256 * (q + 1)); nL[1] = lds32v(aaddr + 256 * (q + 1) + 16); nL[3] = lds32v(aaddr + 256 * (q + 1) + 32);
              nS[0] = lds32v(aaddr + 256 * (q2 - 1)); nS[1] = lds32v(aaddr + 256 * (q2 - 1) + 16); nS[3] = lds32v(aaddr + 256 * (q2 - 1) + 32);
              nL[2] = lds32v(aaddr + 256 * (q + 1) + 16); nS[2] = lds32v(aaddr + 256 * (q2 - 1) + 16);
            }
#pragma unroll
            for (int tau = 15; tau >= 8; --tau) hmma(cacc[tau], aL[0], aL[1], aL[2], aL[3], bf[tau - q][0], bf[tau - q][1]);
#pragma unroll
            for (int tau = 15; tau >= q2; --tau) hmma(cacc[tau], aS[0], aS[1], aS[2], aS[3], bf[tau - q2][0], bf[tau - q2][1]);
#pragma unroll
            for (int tau = 7; tau >= q; --tau) hmma(cacc[tau], aL[0], aL[1], aL[2], aL[3], bf[tau - q][0], bf[tau - q][1]);
#pragma unroll
            for (int i = 0; i < 4; ++i) { aL[i] = nL[i]; aS[i] = nS[i]; }
          }
        }
        if (seg == 2) {
          if (pb >= 0) PROF(pb + 7);
          bar_sync(5 + cc_, 64);
          const uint32_t oth = hb + (1 - hh) * 4096 + lane * 16;
#pragma unroll
          for (int i = 0; i < 8; ++i)
            sts128(oth + i * 512, make_uint4(__float_as_uint(hh ? cacc[i][0] : cacc[8 + i][0]), __float_as_uint(hh ? cacc[i][1] : cacc[8 + i][1]),
                                             __float_as_uint(hh ? cacc[i][2] : cacc[8 + i][2]), __float_as_uint(hh ? cacc[i][3] : cacc[8 + i][3])));
          bar_sync(5 + cc_, 64);
          const uint32_t area = hb + hh * 4096;
          uint32_t yp[8][2];
#pragma unroll
          for (int i = 0; i < 8; ++i) {
            const uint4 v = lds128(area + i * 512 + lane * 16);
            yp[i][0] = pack_bf16((hh ? cacc[8 + i][0] : cacc[i][0]) + __uint_as_float(v.x), (hh ? cacc[8 + i][1] : cacc[i][1]) + __uint_as_float(v.y));
            yp[i][1] = pack_bf16((hh ? cacc[8 + i][2] : cacc[i][2]) + __uint_as_float(v.z), (hh ? cacc[8 + i][3] : cacc[i][3]) + __uint_as_float(v.w));
          }
          __syncwarp();
#pragma unroll
          for (int i = 0; i < 8; i += 2) {
            const uint32_t bl = 8 * (i + (lane >> 4)) + (lane & 7);
            stsm_x4_t(area + 32 * bl + 16 * (((lane >> 3) & 1) ^ ((bl >> 2) & 1)), yp[i][0], yp[i][1], yp[i + 1][0], yp[i + 1][1]);
          }
          fence_async_smem();
          __syncwarp();
          if (lane == 0) mbar_arrive(bar + 8 * B_YFULL);
        }
      }
      if (seg == 2) {
        __syncwarp();
        if (lane == 0) mbar_arrive(bar + 8 * B_CONVDONE);
        if (pb >= 0) PROF(pb + 8);
      }
      const int send = seg == 2 ? 14 : st + (seg == 0 ? SCHED_NS0 : SCHED_NS1);
      const int st0 = st;
      if (seg < 2) {
        if (send > st) bar_sync(3, 256);
      } else if (cw == kap) {
        bar_sync(3, 256);
      }
#pragma unroll 1
      for (; st < send; ++st) {
        if (warp == 4) PROF2(96 + 2 * st);
        mbar_wait(bar + 8 * (B_FULL + rg.slot), rg.phase);
        if (warp == 4) PROF2(96 + 2 * st + 1);
        const uint32_t base = sb + OFF_RING + rg.slot * SLOT_BYTES;
        const uint64_t da = make_desc(base + cw * 8192, 16, 1024);
        const uint64_t db = make_desc(base + 16384, 8192, 1024);
        wg_fence();
#pragma unroll
        for (int kk = 0; kk < 4; ++kk) wgmma_ss_n112(acc2, da + kk * 2, db + kk * 128, (st == 0 && kk == 0) ? 0 : 1);
        wg_commit();
        if (st == 13 - SEND_LEAD_CUT && cw != kap) asm volatile("bar.arrive 3, 256;" ::: "memory");
        if (st > st0) { wg_wait<1>(); release_slot(sb, prev, leader); }
        prev = rg.slot;
        rg.next();
      }
      wg_wait<0>();
      if (st > st0) release_slot(sb, prev, leader);
      if (pb >= 0 && seg < 1) PROF(pb + 9);
    }
    if (pb >= 0) PROF(pb + 10);

    const int t128 = tid & 127;
    if (cw != kap) {
      uint4* dst = reinterpret_cast<uint4*>(g_part) + (size_t)b * 7 * 128 + t128;
#pragma unroll
      for (int q = 0; q < 7; ++q) {
        uint32_t w[4];
#pragma unroll
        for (int i = 0; i < 4; ++i) {
          w[i] = pack_bf16(acc2[8 * q + 2 * i] + 0.0f, acc2[8 * q + 2 * i + 1] + 0.0f) ^ 0x80008000u;
          w[i] = w[i] ? w[i] : 1u;
        }
        asm volatile("st.global.cg.v4.u32 [%0], {%1,%2,%3,%4};" ::"l"(dst + q * 128), "r"(w[0]), "r"(w[1]), "r"(w[2]), "r"(w[3]) : "memory");
      }
      if (pb >= 0) PROF(pb + 11);
    } else {
      uint4* src = reinterpret_cast<uint4*>(g_part) + (size_t)partner * 7 * 128 + t128;
      uint4 pv[7];
      uint32_t it = 0;
#pragma unroll
      for (int q = 0; q < 7; ++q) ld_relaxed_v4(pv[q], src + q * 128);
      if (pb >= 0) PROF(52);
      mbar_wait(bar + 8 * B_EPIFULL, 0);
      if (pb >= 0) PROF(53);
      uint32_t o1[14][2];
      {
        uint32_t em2[2], erh2[2], erl2[2];
#pragma unroll
        for (int rr = 0; rr < 2; ++rr) {
          uint32_t s0, s1;
          asm volatile("ld.shared.v2.u32 {%0,%1}, [%2];" : "=r"(s0), "=r"(s1) : "r"(sb + OFF_STAT + (kap * 64 + wq * 16 + g + 8 * rr) * 8) : "memory");
          em2[rr] = __byte_perm(s0, 0, 0x1010); erh2[rr] = __byte_perm(s0, 0, 0x3232); erl2[rr] = __byte_perm(s1, 0, 0x1010);
        }
        const uint32_t xrow = wq * 16 + (lane & 7) + ((lane >> 3) & 1) * 8;
#pragma unroll
        for (int jn = 0; jn < 14; jn += 2) {
          uint32_t x[4], yv[4];
          const uint32_t chunk = (jn & 7) + (lane >> 4);
          ldsm_x4(x[0], x[1], x[2], x[3], sb + OFF_HST + (jn >> 3) * 8192 + xrow * 128 + ((chunk ^ (xrow & 7)) << 4));
          const uint32_t chrow = 8 * (jn + (lane >> 4)) + (lane & 7);
          const uint32_t tc = (2 * wq + ((lane >> 3) & 1)) ^ kap;
          ldsm_x4_t(yv[0], yv[1], yv[2], yv[3], sb + OFF_C + chrow * 128 + ((tc ^ (chrow & 7)) << 4));
#pragma unroll
          for (int i = 0; i < 4; ++i) {
            const int rr = i & 1;
            const uint32_t d = bsub2(x[i], em2[rr]);
            const uint32_t xn = bfma2(d, erh2[rr], bmul2(d, erl2[rr]));
            o1[jn + (i >> 1)][rr] = badd2(x[i], bmul2(xn, yv[i]));
          }
        }
      }
      if (pb >= 0) PROF(pb + 13);
      while (true) {
        bool ok = true;
#pragma unroll
        for (int q = 0; q < 7; ++q) ok = ok && pv[q].x && pv[q].y && pv[q].z && pv[q].w;
        if (ok || ++it > SPIN_LIMIT) break;
        do { ld_relaxed_v4(pv[6], src + 6 * 128); } while (!(pv[6].x && pv[6].w) && ++it <= SPIN_LIMIT);
#pragma unroll
        for (int q = 0; q < 6; ++q) ld_relaxed_v4(pv[q], src + q * 128);
      }
      if (pb >= 0) PROF(pb + 11);
      const uint32_t xrow2 = wq * 16 + (lane & 7) + ((lane >> 3) & 1) * 8;
#pragma unroll
      for (int jn = 0; jn < 14; jn += 2) {
        const uint32_t pw[4] = {pv[jn >> 1].x ^ 0x80008000u, pv[jn >> 1].y ^ 0x80008000u, pv[jn >> 1].z ^ 0x80008000u, pv[jn >> 1].w ^ 0x80008000u};
        uint32_t o[4];
#pragma unroll
        for (int i = 0; i < 4; ++i) {
          const int q = jn + (i >> 1), rr = i & 1;
          o[i] = badd2(o1[q][rr], pack_bf16(acc2[4 * q + 2 * rr] + __uint_as_float(pw[i] << 16),
                                            acc2[4 * q + 2 * rr + 1] + __uint_as_float(pw[i] & 0xffff0000u)));
        }
        const uint32_t chunk = (jn & 7) + (lane >> 4);
        stsm_x4(sb + OFF_HST + (jn >> 3) * 8192 + xrow2 * 128 + ((chunk ^ (xrow2 & 7)) << 4), o[0], o[1], o[2], o[3]);
      }
      if (pb >= 0) PROF(54);
      fence_async_smem();
      bar_sync(1 + cw, 128);
      if (pb >= 0) PROF(55);
      if (leader) {
        tma3d_store(&P.tm_out, 0, jq, mt * 128 + kap * 64, sb + OFF_HST);
        tma3d_store(&P.tm_out, 64, jq, mt * 128 + kap * 64, sb + OFF_HST + 8192);
        bulk_commit();
        bulk_wait_read0();
        if (b == 0) *(volatile unsigned*)&g_sync.epoch = epoch + 1;
      }
#pragma unroll
      for (int q = 0; q < 7; ++q) src[q * 128] = make_uint4(0, 0, 0, 0);
      if (pb >= 0) PROF(pb + 12);
    }
    cluster_arrive_relaxed();
    cluster_wait();
    if (warp == 4) { PROF(48); PROFG(61); }
  }
}

typedef CUresult (*EncodeFn)(CUtensorMap*, CUtensorMapDataType, cuuint32_t, void*, const cuuint64_t*, const cuuint64_t*,
                             const cuuint32_t*, const cuuint32_t*, CUtensorMapInterleave, CUtensorMapSwizzle,
                             CUtensorMapL2promotion, CUtensorMapFloatOOBfill);

void encode(EncodeFn fn, CUtensorMap* m, const void* base, int rank, const cuuint64_t* dims, const cuuint64_t* strides, const cuuint32_t* box) {
  cuuint32_t es[3] = {1, 1, 1};
  fn(m, CU_TENSOR_MAP_DATA_TYPE_BFLOAT16, (cuuint32_t)rank, const_cast<void*>(base), dims, strides, box, es,
     CU_TENSOR_MAP_INTERLEAVE_NONE, CU_TENSOR_MAP_SWIZZLE_128B, CU_TENSOR_MAP_L2_PROMOTION_L2_128B, CU_TENSOR_MAP_FLOAT_OOB_FILL_NONE);
}
void encode2(EncodeFn fn, CUtensorMap* m, const void* base, uint64_t cols, uint64_t rows, uint32_t bc, uint32_t br) {
  cuuint64_t d[2] = {cols, rows}; cuuint64_t s[1] = {cols * 2}; cuuint32_t bx[2] = {bc, br};
  encode(fn, m, base, 2, d, s, bx);
}
void encode3(EncodeFn fn, CUtensorMap* m, const void* base, uint64_t w, uint64_t nslice, uint64_t rows, uint32_t bc, uint32_t br) {
  cuuint64_t d[3] = {w, nslice, rows}; cuuint64_t s[2] = {w * 2, w * nslice * 2}; cuuint32_t bx[3] = {bc, 1, br};
  encode(fn, m, base, 3, d, s, bx);
}

}

extern "C" void kernel_launch(void* const* d_in, const int* in_sizes, int n_in, void* d_out, int out_size) {
  (void)in_sizes; (void)n_in; (void)out_size;
  static EncodeFn fn = nullptr;
  if (!fn) {
    void* p = nullptr;
    cudaDriverEntryPointQueryResult qr;
    cudaGetDriverEntryPoint("cuTensorMapEncodeTiled", &p, cudaEnableDefault, &qr);
    fn = (EncodeFn)p;
    cudaFuncSetAttribute(fused_h3_mlp_kernel, cudaFuncAttributeMaxDynamicSharedMemorySize, SMEM_BYTES);
  }
  void *h, *y2;
  cudaGetSymbolAddress(&h, g_h);
  cudaGetSymbolAddress(&y2, g_y2T);
  Params P;
  const void* x = d_in[0];
  encode2(fn, &P.tm_x, x, D_DIM, S_LEN, 64, 128);
  encode3(fn, &P.tm_wg, d_in[7], 224, 8, D_DIM, 64, 112);
  encode3(fn, &P.tm_wu, d_in[8], 224, 8, D_DIM, 64, 112);
  encode3(fn, &P.tm_hs, h, 224, 8, S_LEN, 64, 64);
  encode3(fn, &P.tm_hh, h, 32, 56, S_LEN, 64, 64);
  encode2(fn, &P.tm_hl, h, F_DIM, S_LEN, 64, 128);
  encode3(fn, &P.tm_wd, d_in[9], 112, 4, F_DIM, 64, 64);
  encode2(fn, &P.tm_xe, x, D_DIM, S_LEN, 64, 64);
  encode2(fn, &P.tm_y, y2, S_LEN, D_DIM, 64, 112);
  encode3(fn, &P.tm_out, d_out, 112, 4, S_LEN, 64, 64);
  P.k = (const __nv_bfloat16*)d_in[1];
  P.v = (const __nv_bfloat16*)d_in[2];
  P.shift_k = (const __nv_bfloat16*)d_in[3];
  P.ssm_k = (const __nv_bfloat16*)d_in[4];
  P.ssm_D = (const __nv_bfloat16*)d_in[5];
  P.wg = (const __nv_bfloat16*)d_in[7];
  P.wu = (const __nv_bfloat16*)d_in[8];
  P.wd = (const __nv_bfloat16*)d_in[9];
  P.out = (__nv_bfloat16*)d_out;
  fused_h3_mlp_kernel<<<NCTA, NTHREADS, SMEM_BYTES>>>(P);
}
```

```cpp
#include <cuda_runtime.h>
#include <cuda_bf16.h>
#include <cuda.h>
#include <stdint.h>

namespace {

constexpr int S_LEN = 2048;
constexpr int D_DIM = 448;
constexpr int F_DIM = 1792;
constexpr int NCTA  = 128;
constexpr int NTHREADS = 384;
constexpr int CONV_CTAS = 112;

constexpr uint32_t SLOT_BYTES = 32768;
constexpr int      NSLOT      = 5;
constexpr uint32_t OFF_RING = 0;
constexpr uint32_t OFF_HST  = NSLOT * SLOT_BYTES;
constexpr uint32_t OFF_C    = OFF_HST + 16384;
constexpr uint32_t U_BYTES  = 4352;
constexpr uint32_t HC_BYTES = 8320;
constexpr uint32_t HC_COPY0 = 4160;
constexpr uint32_t OFF_U    = OFF_C;
constexpr uint32_t OFF_HC   = OFF_C + 4 * U_BYTES;
constexpr uint32_t OFF_KST  = OFF_U;
constexpr uint32_t OFF_VTAIL = 28672;
constexpr uint32_t OFF_MISC = OFF_HC + 4 * HC_BYTES;
constexpr uint32_t OFF_BAR  = OFF_MISC;
constexpr uint32_t OFF_DV   = OFF_MISC + 256;
constexpr uint32_t OFF_STAT = OFF_MISC + 512;
constexpr uint32_t SMEM_BYTES = OFF_STAT + 1024;
static_assert(SMEM_BYTES <= 232448, "smem");

constexpr int B_FULL = 0, B_EMPTY = 5, B_XFULL = 10, B_HRAW = 17, B_CONVRDY = 18, B_EPIFULL = 19,
              B_KVFULL = 20, B_HSTF = 21, B_HSTE = 23, B_YFULL = 25, B_CONVDONE = 26, B_XFREE = 27, B_XFULL2 = 28;

struct alignas(64) Params {
  CUtensorMap tm_wg;
  CUtensorMap tm_wu;
  CUtensorMap tm_hs;
  CUtensorMap tm_hh;
  CUtensorMap tm_hl;
  CUtensorMap tm_wd;
  CUtensorMap tm_xe;
  CUtensorMap tm_y;
  CUtensorMap tm_yl;
  CUtensorMap tm_kv;
  CUtensorMap tm_out;
  const __nv_bfloat16* k;
  const __nv_bfloat16* v;
  const __nv_bfloat16* shift_k;
  const __nv_bfloat16* ssm_k;
  const __nv_bfloat16* ssm_D;
  const __nv_bfloat16* wg;
  const __nv_bfloat16* wu;
  const __nv_bfloat16* wd;
  __nv_bfloat16* out;
};

__device__ __align__(1024) __nv_bfloat16 g_h[S_LEN * F_DIM];
__device__ __align__(1024) __nv_bfloat16 g_kvT[D_DIM * S_LEN];
__device__ __align__(1024) __nv_bfloat16 g_y2T[D_DIM * S_LEN];
struct Sync {
  unsigned epoch;      unsigned pad0[31];
  unsigned cnt_kv;     unsigned pad1[31];
  unsigned cnt_h[32 * 32];
  unsigned cnt_y[4 * 32];
};
__device__ __align__(1024) Sync g_sync;

__device__ __forceinline__ int fresh_tid() { int t; asm volatile("mov.u32 %0, %%tid.x;" : "=r"(t)); return t; }
__device__ __forceinline__ uint32_t smem_u32(const void* p) { return (uint32_t)__cvta_generic_to_shared(p); }
__device__ __forceinline__ void mbar_init(uint32_t a, uint32_t c) { asm volatile("mbarrier.init.shared::cta.b64 [%0], %1;" ::"r"(a), "r"(c)); }
__device__ __forceinline__ void mbar_expect_tx(uint32_t a, uint32_t bytes) {
  asm volatile("mbarrier.arrive.expect_tx.shared::cta.b64 _, [%0], %1;" ::"r"(a), "r"(bytes) : "memory");
}
__device__ __forceinline__ void mbar_arrive(uint32_t a) { asm volatile("mbarrier.arrive.shared::cta.b64 _, [%0];" ::"r"(a) : "memory"); }
__device__ __forceinline__ void mbar_arrive_cta(uint32_t a, uint32_t cta) {
  asm volatile("{\n.reg .b32 r;\nmapa.shared::cluster.u32 r, %0, %1;\nmbarrier.arrive.shared::cluster.b64 _, [r];\n}" ::"r"(a), "r"(cta) : "memory");
}
__device__ __forceinline__ bool mbar_try(uint32_t a, uint32_t ph) {
  uint32_t ok;
  asm volatile("{\n.reg .pred p;\nmbarrier.try_wait.parity.shared::cta.b64 p, [%1], %2;\nselp.u32 %0, 1, 0, p;\n}" : "=r"(ok) : "r"(a), "r"(ph) : "memory");
  return ok != 0;
}
#define WAIT_HINT_NS 2000u
constexpr uint32_t SPIN_LIMIT = 1u << 20;
__device__ __forceinline__ void mbar_wait(uint32_t a, uint32_t ph) {
  if (mbar_try(a, ph)) return;
  uint32_t it = 0;
  while (!mbar_try(a, ph)) { if (++it > SPIN_LIMIT) break; }
}
__device__ __forceinline__ void mbar_wait_parked(uint32_t a, uint32_t ph) {
  uint32_t it = 0, ok;
  do {
    asm volatile("{\n.reg .pred p;\nmbarrier.try_wait.parity.shared::cta.b64 p, [%1], %2, %3;\nselp.u32 %0, 1, 0, p;\n}"
                 : "=r"(ok) : "r"(a), "r"(ph), "r"(WAIT_HINT_NS) : "memory");
  } while (!ok && ++it <= SPIN_LIMIT);
}
__device__ __forceinline__ unsigned ld_acquire(const unsigned* p) {
  unsigned v; asm volatile("ld.acquire.gpu.global.u32 %0, [%1];" : "=r"(v) : "l"(p) : "memory"); return v;
}
__device__ __forceinline__ unsigned ld_relaxed(const unsigned* p) {
  unsigned v; asm volatile("ld.relaxed.gpu.global.u32 %0, [%1];" : "=r"(v) : "l"(p) : "memory"); return v;
}
__device__ __forceinline__ void wait_count(const unsigned* p, unsigned target) {
  uint32_t it = 0;
  while ((int)(ld_acquire(p) - target) < 0) { if (++it > SPIN_LIMIT) break; }
}
__device__ __forceinline__ void red_release_add(unsigned* p, unsigned v) {
  asm volatile("red.release.gpu.global.add.u32 [%0], %1;" ::"l"(p), "r"(v) : "memory");
}
__device__ __forceinline__ void st_release(unsigned* p, unsigned v) {
  asm volatile("st.release.gpu.global.u32 [%0], %1;" ::"l"(p), "r"(v) : "memory");
}
__device__ __forceinline__ bool elect_one() {
  uint32_t p;
  asm volatile("{\n.reg .pred P;\nelect.sync _|P, 0xffffffff;\nselp.u32 %0, 1, 0, P;\n}" : "=r"(p));
  return p != 0;
}
__device__ __forceinline__ void bar_sync(int id, int n) { asm volatile("bar.sync %0, %1;" ::"r"(id), "r"(n) : "memory"); }
__device__ __forceinline__ void fence_async_smem() { asm volatile("fence.proxy.async.shared::cta;" ::: "memory"); }
__device__ __forceinline__ void fence_async_global() { asm volatile("fence.proxy.async.global;" ::: "memory"); }
__device__ __forceinline__ void cluster_arrive_relaxed() { asm volatile("barrier.cluster.arrive.relaxed.aligned;" ::: "memory"); }
__device__ __forceinline__ void cluster_wait() { asm volatile("barrier.cluster.wait.acquire.aligned;" ::: "memory"); }

__device__ __forceinline__ void tma2d(uint32_t dst, const CUtensorMap* m, int c0, int c1, uint32_t bar) {
  asm volatile("cp.async.bulk.tensor.2d.shared::cluster.global.mbarrier::complete_tx::bytes [%0], [%1, {%3, %4}], [%2];"
               ::"r"(dst), "l"(m), "r"(bar), "r"(c0), "r"(c1) : "memory");
}
__device__ __forceinline__ void tma2d_mc(uint32_t dst, const CUtensorMap* m, int c0, int c1, uint32_t bar) {
  asm volatile("cp.async.bulk.tensor.2d.shared::cluster.global.mbarrier::complete_tx::bytes.multicast::cluster [%0], [%1, {%3, %4}], [%2], %5;"
               ::"r"(dst), "l"(m), "r"(bar), "r"(c0), "r"(c1), "h"((uint16_t)3) : "memory");
}
__device__ __forceinline__ void tma3d(uint32_t dst, const CUtensorMap* m, int c0, int c1, int c2, uint32_t bar) {
  asm volatile("cp.async.bulk.tensor.3d.shared::cluster.global.mbarrier::complete_tx::bytes [%0], [%1, {%3, %4, %5}], [%2];"
               ::"r"(dst), "l"(m), "r"(bar), "r"(c0), "r"(c1), "r"(c2) : "memory");
}
__device__ __forceinline__ uint32_t mapa(uint32_t a, uint32_t cta) { uint32_t r; asm("mapa.shared::cluster.u32 %0, %1, %2;" : "=r"(r) : "r"(a), "r"(cta)); return r; }
__device__ __forceinline__ void st_async_v4(uint32_t dst, uint32_t a, uint32_t b, uint32_t c, uint32_t d, uint32_t bar) {
  asm volatile("st.async.weak.shared::cluster.mbarrier::complete_tx::bytes.v4.b32 [%0], {%1,%2,%3,%4}, [%5];"
               ::"r"(dst), "r"(a), "r"(b), "r"(c), "r"(d), "r"(bar) : "memory");
}
__device__ __forceinline__ void tma3d_mc(uint32_t dst, const CUtensorMap* m, int c0, int c1, int c2, uint32_t bar) {
  asm volatile("cp.async.bulk.tensor.3d.shared::cluster.global.mbarrier::complete_tx::bytes.multicast::cluster [%0], [%1, {%3, %4, %5}], [%2], %6;"
               ::"r"(dst), "l"(m), "r"(bar), "r"(c0), "r"(c1), "r"(c2), "h"((uint16_t)3) : "memory");
}
__device__ __forceinline__ void tma2d_store(const CUtensorMap* m, int c0, int c1, uint32_t src) {
  asm volatile("cp.async.bulk.tensor.2d.global.shared::cta.bulk_group [%0, {%2, %3}], [%1];"
               ::"l"(m), "r"(src), "r"(c0), "r"(c1) : "memory");
}
__device__ __forceinline__ void tma3d_prefetch(const CUtensorMap* m, int c0, int c1, int c2) {
  asm volatile("cp.async.bulk.prefetch.tensor.3d.L2.global [%0, {%1, %2, %3}];" ::"l"(m), "r"(c0), "r"(c1), "r"(c2) : "memory");
}
__device__ __forceinline__ void tma3d_store(const CUtensorMap* m, int c0, int c1, int c2, uint32_t src) {
  asm volatile("cp.async.bulk.tensor.3d.global.shared::cta.bulk_group [%0, {%2, %3, %4}], [%1];"
               ::"l"(m), "r"(src), "r"(c0), "r"(c1), "r"(c2) : "memory");
}
__device__ __forceinline__ void bulk_g2s(uint32_t dst, const void* src, uint32_t bytes, uint32_t bar) {
  asm volatile("cp.async.bulk.shared::cluster.global.mbarrier::complete_tx::bytes [%0], [%1], %2, [%3];"
               ::"r"(dst), "l"(src), "r"(bytes), "r"(bar) : "memory");
}
__device__ __forceinline__ void bulk_s2g(void* dst, uint32_t src, uint32_t bytes) {
  asm volatile("cp.async.bulk.global.shared::cta.bulk_group [%0], [%1], %2;" ::"l"(dst), "r"(src), "r"(bytes) : "memory");
}
__device__ __forceinline__ void l2_prefetch(const void* src, uint32_t bytes) {
  asm volatile("cp.async.bulk.prefetch.L2.global [%0], %1;" ::"l"(src), "r"(bytes) : "memory");
}
__device__ __forceinline__ void red_relaxed_add(unsigned* p, unsigned v) {
  asm volatile("red.relaxed.gpu.global.add.u32 [%0], %1;" ::"l"(p), "r"(v) : "memory");
}
__device__ __forceinline__ void bulk_commit() { asm volatile("cp.async.bulk.commit_group;" ::: "memory"); }
__device__ __forceinline__ void bulk_wait_read0() { asm volatile("cp.async.bulk.wait_group.read 0;" ::: "memory"); }
__device__ __forceinline__ void bulk_wait0() { asm volatile("cp.async.bulk.wait_group 0;" ::: "memory"); }
__device__ __forceinline__ void prefetch_tmap(const CUtensorMap* m) { asm volatile("prefetch.tensormap [%0];" ::"l"(m) : "memory"); }

__device__ __forceinline__ void wg_fence() { asm volatile("wgmma.fence.sync.aligned;" ::: "memory"); }
__device__ __forceinline__ void wg_commit() { asm volatile("wgmma.commit_group.sync.aligned;" ::: "memory"); }
template <int N> __device__ __forceinline__ void wg_wait() { asm volatile("wgmma.wait_group.sync.aligned %0;" ::"n"(N) : "memory"); }
__device__ __forceinline__ uint64_t make_desc(uint32_t addr, uint32_t lbo, uint32_t sbo) {
  return (uint64_t)((addr & 0x3FFFF) >> 4) | ((uint64_t)(lbo >> 4) << 16) | ((uint64_t)(sbo >> 4) << 32) | (1ull << 62);
}
__device__ __forceinline__ void ldsm_x4(uint32_t (&r)[4], uint32_t a) {
  asm volatile("ldmatrix.sync.aligned.m8n8.x4.shared.b16 {%0,%1,%2,%3}, [%4];" : "=r"(r[0]), "=r"(r[1]), "=r"(r[2]), "=r"(r[3]) : "r"(a) : "memory");
}
__device__ __forceinline__ void ldsm_x4(uint32_t& r0, uint32_t& r1, uint32_t& r2, uint32_t& r3, uint32_t a) {
  asm volatile("ldmatrix.sync.aligned.m8n8.x4.shared.b16 {%0,%1,%2,%3}, [%4];" : "=r"(r0), "=r"(r1), "=r"(r2), "=r"(r3) : "r"(a) : "memory");
}
__device__ __forceinline__ void ldsm_x4_t(uint32_t& r0, uint32_t& r1, uint32_t& r2, uint32_t& r3, uint32_t a) {
  asm volatile("ldmatrix.sync.aligned.m8n8.x4.trans.shared.b16 {%0,%1,%2,%3}, [%4];" : "=r"(r0), "=r"(r1), "=r"(r2), "=r"(r3) : "r"(a) : "memory");
}
__device__ __forceinline__ void ldsm_x2(uint32_t& r0, uint32_t& r1, uint32_t a) {
  asm volatile("ldmatrix.sync.aligned.m8n8.x2.shared.b16 {%0,%1}, [%2];" : "=r"(r0), "=r"(r1) : "r"(a) : "memory");
}
__device__ __forceinline__ void ldsm_x2_t(uint32_t& r0, uint32_t& r1, uint32_t a) {
  asm volatile("ldmatrix.sync.aligned.m8n8.x2.trans.shared.b16 {%0,%1}, [%2];" : "=r"(r0), "=r"(r1) : "r"(a) : "memory");
}
__device__ __forceinline__ void stsm_x4(uint32_t a, uint32_t r0, uint32_t r1, uint32_t r2, uint32_t r3) {
  asm volatile("stmatrix.sync.aligned.m8n8.x4.shared.b16 [%0], {%1,%2,%3,%4};" ::"r"(a), "r"(r0), "r"(r1), "r"(r2), "r"(r3) : "memory");
}
__device__ __forceinline__ void stsm_x2(uint32_t a, uint32_t r0, uint32_t r1) {
  asm volatile("stmatrix.sync.aligned.m8n8.x2.shared.b16 [%0], {%1,%2};" ::"r"(a), "r"(r0), "r"(r1) : "memory");
}
__device__ __forceinline__ void stsm_x4_t(uint32_t a, uint32_t r0, uint32_t r1, uint32_t r2, uint32_t r3) {
  asm volatile("stmatrix.sync.aligned.m8n8.x4.trans.shared.b16 [%0], {%1,%2,%3,%4};" ::"r"(a), "r"(r0), "r"(r1), "r"(r2), "r"(r3) : "memory");
}
__device__ __forceinline__ void hmma(float (&c)[4], uint32_t a0, uint32_t a1, uint32_t a2, uint32_t a3, uint32_t b0, uint32_t b1) {
  asm volatile("mma.sync.aligned.m16n8k16.row.col.f32.bf16.bf16.f32 {%0,%1,%2,%3}, {%4,%5,%6,%7}, {%8,%9}, {%0,%1,%2,%3};"
               : "+f"(c[0]), "+f"(c[1]), "+f"(c[2]), "+f"(c[3]) : "r"(a0), "r"(a1), "r"(a2), "r"(a3), "r"(b0), "r"(b1));
}
__device__ __forceinline__ uint32_t lds32(uint32_t a) { uint32_t v; asm volatile("ld.shared.u32 %0, [%1];" : "=r"(v) : "r"(a) : "memory"); return v; }
__device__ __forceinline__ uint32_t lds32v(uint32_t a) { uint32_t v; asm volatile("ld.volatile.shared.u32 %0, [%1];" : "=r"(v) : "r"(a) : "memory"); return v; }
__device__ __forceinline__ void ld_relaxed_v4(uint4& v, const uint4* p) {
  asm volatile("ld.relaxed.gpu.global.v4.u32 {%0,%1,%2,%3}, [%4];" : "=r"(v.x), "=r"(v.y), "=r"(v.z), "=r"(v.w) : "l"(p) : "memory");
}
__device__ __forceinline__ uint4 lds128(uint32_t a) {
  uint4 v; asm volatile("ld.shared.v4.u32 {%0,%1,%2,%3}, [%4];" : "=r"(v.x), "=r"(v.y), "=r"(v.z), "=r"(v.w) : "r"(a) : "memory"); return v;
}
__device__ __forceinline__ void sts128(uint32_t a, uint4 v) {
  asm volatile("st.shared.v4.u32 [%0], {%1,%2,%3,%4};" ::"r"(a), "r"(v.x), "r"(v.y), "r"(v.z), "r"(v.w) : "memory");
}
__device__ __forceinline__ void sts64(uint32_t a, uint32_t x, uint32_t y) { asm volatile("st.shared.v2.u32 [%0], {%1,%2};" ::"r"(a), "r"(x), "r"(y) : "memory"); }
__device__ __forceinline__ uint32_t bmul2(uint32_t a, uint32_t b) { uint32_t d; asm("mul.rn.bf16x2 %0, %1, %2;" : "=r"(d) : "r"(a), "r"(b)); return d; }
__device__ __forceinline__ uint32_t badd2(uint32_t a, uint32_t b) { uint32_t d; asm("add.rn.bf16x2 %0, %1, %2;" : "=r"(d) : "r"(a), "r"(b)); return d; }
__device__ __forceinline__ uint32_t bsub2(uint32_t a, uint32_t b) { uint32_t d; asm("sub.rn.bf16x2 %0, %1, %2;" : "=r"(d) : "r"(a), "r"(b)); return d; }
__device__ __forceinline__ uint32_t bfma2(uint32_t a, uint32_t b, uint32_t c) { uint32_t d; asm("fma.rn.bf16x2 %0, %1, %2, %3;" : "=r"(d) : "r"(a), "r"(b), "r"(c)); return d; }
__device__ __forceinline__ uint32_t bmax2(uint32_t a, uint32_t b) { uint32_t d; asm("max.bf16x2 %0, %1, %2;" : "=r"(d) : "r"(a), "r"(b)); return d; }
__device__ __forceinline__ uint32_t pack_bf16(float lo, float hi) { uint32_t d; asm("cvt.rn.bf16x2.f32 %0, %1, %2;" : "=r"(d) : "f"(hi), "f"(lo)); return d; }
__device__ __forceinline__ float bf16_round(float x) { return __bfloat162float(__float2bfloat16_rn(x)); }
__device__ __forceinline__ uint32_t tag_word(uint32_t w) { w ^= 0x80008000u; return w ? w : 1u; }
__device__ __forceinline__ uint32_t tag_elems(uint32_t w) { return bfma2(w, 0x3F803F80u, 0u) ^ 0x80008000u; }
__device__ __forceinline__ float sqrt_approx(float x) { float y; asm("sqrt.approx.f32 %0, %1;" : "=f"(y) : "f"(x)); return y; }
__device__ __forceinline__ float rcp_approx(float x) { float y; asm("rcp.approx.f32 %0, %1;" : "=f"(y) : "f"(x)); return y; }
__device__ __forceinline__ uint32_t dup_bf16(float x) { return pack_bf16(x, x); }

__device__ __forceinline__ void wgmma_rs_n128(float (&d)[64], const uint32_t (&a)[4], uint64_t db, int sc) {
  asm volatile("{\n.reg .pred p;\nsetp.ne.b32 p, %69, 0;\n"
    "wgmma.mma_async.sync.aligned.m64n128k16.f32.bf16.bf16 "
    "{%0,%1,%2,%3,%4,%5,%6,%7,%8,%9,%10,%11,%12,%13,%14,%15,%16,%17,%18,%19,%20,%21,%22,%23,%24,%25,%26,%27,%28,%29,%30,%31,%32,%33,%34,%35,%36,%37,%38,%39,%40,%41,%42,%43,%44,%45,%46,%47,%48,%49,%50,%51,%52,%53,%54,%55,%56,%57,%58,%59,%60,%61,%62,%63}, "
    "{%64,%65,%66,%67}, %68, p, 1, 1, 1;\n}\n"
    : "+f"(d[0]),"+f"(d[1]),"+f"(d[2]),"+f"(d[3]),"+f"(d[4]),"+f"(d[5]),"+f"(d[6]),"+f"(d[7]),"+f"(d[8]),"+f"(d[9]),"+f"(d[10]),"+f"(d[11]),"+f"(d[12]),"+f"(d[13]),"+f"(d[14]),"+f"(d[15]),"+f"(d[16]),"+f"(d[17]),"+f"(d[18]),"+f"(d[19]),"+f"(d[20]),"+f"(d[21]),"+f"(d[22]),"+f"(d[23]),"+f"(d[24]),"+f"(d[25]),"+f"(d[26]),"+f"(d[27]),"+f"(d[28]),"+f"(d[29]),"+f"(d[30]),"+f"(d[31]),"+f"(d[32]),"+f"(d[33]),"+f"(d[34]),"+f"(d[35]),"+f"(d[36]),"+f"(d[37]),"+f"(d[38]),"+f"(d[39]),"+f"(d[40]),"+f"(d[41]),"+f"(d[42]),"+f"(d[43]),"+f"(d[44]),"+f"(d[45]),"+f"(d[46]),"+f"(d[47]),"+f"(d[48]),"+f"(d[49]),"+f"(d[50]),"+f"(d[51]),"+f"(d[52]),"+f"(d[53]),"+f"(d[54]),"+f"(d[55]),"+f"(d[56]),"+f"(d[57]),"+f"(d[58]),"+f"(d[59]),"+f"(d[60]),"+f"(d[61]),"+f"(d[62]),"+f"(d[63])
    : "r"(a[0]),"r"(a[1]),"r"(a[2]),"r"(a[3]),"l"(db),"r"(sc));
}
__device__ __forceinline__ void wgmma_rs_n32(float (&d)[16], const uint32_t (&a)[4], uint64_t db, int sc) {
  asm volatile("{\n.reg .pred p;\nsetp.ne.b32 p, %21, 0;\n"
    "wgmma.mma_async.sync.aligned.m64n32k16.f32.bf16.bf16 "
    "{%0,%1,%2,%3,%4,%5,%6,%7,%8,%9,%10,%11,%12,%13,%14,%15}, "
    "{%16,%17,%18,%19}, %20, p, 1, 1, 1;\n}\n"
    : "+f"(d[0]),"+f"(d[1]),"+f"(d[2]),"+f"(d[3]),"+f"(d[4]),"+f"(d[5]),"+f"(d[6]),"+f"(d[7]),"+f"(d[8]),"+f"(d[9]),"+f"(d[10]),"+f"(d[11]),"+f"(d[12]),"+f"(d[13]),"+f"(d[14]),"+f"(d[15])
    : "r"(a[0]),"r"(a[1]),"r"(a[2]),"r"(a[3]),"l"(db),"r"(sc));
}
__device__ __forceinline__ void wgmma_ss_n112(float (&d)[56], uint64_t da, uint64_t db, int sc) {
  asm volatile("{\n.reg .pred p;\nsetp.ne.b32 p, %58, 0;\n"
    "wgmma.mma_async.sync.aligned.m64n112k16.f32.bf16.bf16 "
    "{%0,%1,%2,%3,%4,%5,%6,%7,%8,%9,%10,%11,%12,%13,%14,%15,%16,%17,%18,%19,%20,%21,%22,%23,%24,%25,%26,%27,%28,%29,%30,%31,%32,%33,%34,%35,%36,%37,%38,%39,%40,%41,%42,%43,%44,%45,%46,%47,%48,%49,%50,%51,%52,%53,%54,%55}, "
    "%56, %57, p, 1, 1, 0, 1;\n}\n"
    : "+f"(d[0]),"+f"(d[1]),"+f"(d[2]),"+f"(d[3]),"+f"(d[4]),"+f"(d[5]),"+f"(d[6]),"+f"(d[7]),"+f"(d[8]),"+f"(d[9]),"+f"(d[10]),"+f"(d[11]),"+f"(d[12]),"+f"(d[13]),"+f"(d[14]),"+f"(d[15]),"+f"(d[16]),"+f"(d[17]),"+f"(d[18]),"+f"(d[19]),"+f"(d[20]),"+f"(d[21]),"+f"(d[22]),"+f"(d[23]),"+f"(d[24]),"+f"(d[25]),"+f"(d[26]),"+f"(d[27]),"+f"(d[28]),"+f"(d[29]),"+f"(d[30]),"+f"(d[31]),"+f"(d[32]),"+f"(d[33]),"+f"(d[34]),"+f"(d[35]),"+f"(d[36]),"+f"(d[37]),"+f"(d[38]),"+f"(d[39]),"+f"(d[40]),"+f"(d[41]),"+f"(d[42]),"+f"(d[43]),"+f"(d[44]),"+f"(d[45]),"+f"(d[46]),"+f"(d[47]),"+f"(d[48]),"+f"(d[49]),"+f"(d[50]),"+f"(d[51]),"+f"(d[52]),"+f"(d[53]),"+f"(d[54]),"+f"(d[55])
    : "l"(da),"l"(db),"r"(sc));
}

#define PROF(slot) do {} while (0)
#define PROFG(slot) do {} while (0)
#define PROF2(slot) do {} while (0)

#define TOUCH_PART 0
#define SCHED_NR0 3
#define SCHED_NS0 5
#define SCHED_NR1 1
#define SCHED_NS1 4
#define SYNC_CHUNK 1
#define XST_MODE 1
#define XST "st.global.cg.v4.u32"
#define MAP_MODE 1
#define SEND_LEAD_CUT 0
#define PROD_WAIT mbar_wait_parked
#define XCHG_DELAY 800
#define XSEND_FIRST 0
#define SCHED_FSEG 2
#define LAG_EVERY_PASS 0
#define LAG_STAGE 1
#define EXP_NOAUX 0
#define L2PROMO 2
#define PF_W0 0
__device__ __forceinline__ int wcol(int p, int f) { return (f & 1) ? (p < 3 ? 32 + 64 * p : -32) : 64 * p; }

struct Ring {
  uint32_t slot, phase;
  __device__ __forceinline__ void next() { if (++slot == NSLOT) { slot = 0; phase ^= 1; } }
};

__device__ __forceinline__ void release_slot(uint32_t sb, uint32_t slot, bool leader) {
  if (leader) mbar_arrive(sb + OFF_BAR + 8 * (B_EMPTY + slot));
}

template <int MODE>
__device__ __forceinline__ void gemm1_pass(float (&acc)[64], float (&ag)[16], float (&au)[16], uint32_t (&xa)[28][4],
                                           const uint32_t (&m2)[2], const uint32_t (&rh2)[2], const uint32_t (&rl2)[2],
                                           Ring& rg, uint32_t sb, bool leader, int cw, int pslot, uint32_t hoff, int lane) {
  uint32_t prev = 0;
#pragma unroll
  for (int s = 0; s < 4; ++s) {
    if (MODE == 0) {
#pragma unroll
      for (int kk = 7 * s; kk < 7 * s + 7; ++kk) {
#pragma unroll
        for (int i = 0; i < 4; ++i) {
          const uint32_t d = bsub2(xa[kk][i], m2[i & 1]);
          xa[kk][i] = bfma2(d, rh2[i & 1], bmul2(d, rl2[i & 1]));
        }
      }
    }
    if (s == 0 && cw == 1 && (MODE == 0 || LAG_EVERY_PASS)) bar_sync(3, 256);
    if (pslot >= 0) PROF2(pslot + 2 * s);
    mbar_wait(sb + OFF_BAR + 8 * (B_FULL + rg.slot), rg.phase);
    if (pslot >= 0) PROF2(pslot + 2 * s + 1);
    const uint32_t base = sb + OFF_RING + rg.slot * SLOT_BYTES;
    const uint64_t db = make_desc(base + (MODE == 2 ? hoff : 0u), 14336, 1024);
    wg_fence();
#pragma unroll
    for (int kk = 0; kk < 7; ++kk) {
      const int sc = (s == 0 && kk == 0) ? 0 : 1;
      if (MODE != 2) {
        wgmma_rs_n128(acc, xa[7 * s + kk], db + kk * 128, sc);
      } else {
        wgmma_rs_n32(ag, xa[7 * s + kk], db + kk * 128, sc);
        wgmma_rs_n32(au, xa[7 * s + kk], db + kk * 128 + (14336 >> 4), sc);
      }
    }
    wg_commit();
    if (s == LAG_STAGE && cw == 0 && (MODE == 0 || LAG_EVERY_PASS)) asm volatile("bar.arrive 3, 256;" ::: "memory");
    if (MODE != 0 && s == 0) {
      fence_async_smem();
      __syncwarp();
      if (lane == 0) mbar_arrive(sb + OFF_BAR + 8 * (B_HSTF + cw));
    }
    if (s > 0) { wg_wait<1>(); release_slot(sb, prev, leader); }
    prev = rg.slot;
    rg.next();
  }
  wg_wait<0>();
  release_slot(sb, prev, leader);
}

__device__ __forceinline__ void gemm2_chunk(float (&acc2)[56], int& st, int send, Ring& rg, uint32_t sb, bool leader, int cw) {
  const int st0 = st;
  uint32_t prev = 0;
#pragma unroll 1
  for (; st < send; ++st) {
    mbar_wait(sb + OFF_BAR + 8 * (B_FULL + rg.slot), rg.phase);
    const uint32_t base = sb + OFF_RING + rg.slot * SLOT_BYTES;
    const uint64_t da = make_desc(base + cw * 8192, 16, 1024);
    const uint64_t db = make_desc(base + 16384, 8192, 1024);
    wg_fence();
#pragma unroll
    for (int kk = 0; kk < 4; ++kk) wgmma_ss_n112(acc2, da + kk * 2, db + kk * 128, (st == 0 && kk == 0) ? 0 : 1);
    wg_commit();
    if (st > st0) { wg_wait<1>(); release_slot(sb, prev, leader); }
    prev = rg.slot;
    rg.next();
  }
  wg_wait<0>();
  if (st > st0) release_slot(sb, prev, leader);
}

template <int NG>
__device__ __forceinline__ void gemm1_stage_h(const float* gate, const float* up, uint32_t saddr, uint32_t srow, int lane, uint32_t choff) {
#pragma unroll
  for (int j = 0; j < NG; j += 2) {
    uint32_t h[4];
#pragma unroll
    for (int i = 0; i < 4; ++i) {
      const int o = 4 * (j + (i >> 1)) + 2 * (i & 1);
      h[i] = bmul2(bmax2(pack_bf16(gate[o], gate[o + 1]), 0u), pack_bf16(up[o], up[o + 1]));
    }
    stsm_x4(saddr + (((choff + j + (lane >> 4)) ^ (srow & 7)) << 4), h[0], h[1], h[2], h[3]);
  }
}

__device__ __forceinline__ void kv_prepass(uint32_t ka, uint32_t va, uint32_t stg, const uint4 w0, int b, int cp) {
  const uint32_t t0 = __byte_perm(w0.x, w0.z, 0x5410), t1 = __byte_perm(w0.x, w0.z, 0x7632);
  const uint32_t t2 = __byte_perm(w0.y, w0.w, 0x5410), t3 = __byte_perm(w0.y, w0.w, 0x7632);
  uint32_t kr[19], vr[16];
#pragma unroll
  for (int i = 0; i < 19; ++i) kr[i] = lds32(ka + cp * 4 + i * 896);
#pragma unroll
  for (int i = 0; i < 16; ++i) vr[i] = lds32(va + cp * 4 + (i >> 2) * SLOT_BYTES + (i & 3) * 896);
  uint32_t o0[8], o1[8];
#pragma unroll
  for (int i = 0; i < 16; i += 2) {
    uint32_t kv[2];
#pragma unroll
    for (int e = 0; e < 2; ++e) {
      uint32_t a = bmul2(kr[i + e], t3);
      a = badd2(a, bmul2(kr[i + e + 1], t2));
      a = badd2(a, bmul2(kr[i + e + 2], t1));
      a = badd2(a, bmul2(kr[i + e + 3], t0));
      kv[e] = bmul2(a, vr[i + e]);
    }
    o0[7 - (i >> 1)] = __byte_perm(kv[1], kv[0], 0x5410);
    o1[7 - (i >> 1)] = __byte_perm(kv[1], kv[0], 0x7632);
  }
  const int c = (2 * cp) / 112;
  const uint32_t dst = stg + c * HC_BYTES + (2 * cp - 112 * c) * 32;
  const uint32_t sw = ((b >> 2) & 1) * 16;
  sts128(dst + sw,             make_uint4(o0[0], o0[1], o0[2], o0[3]));
  sts128(dst + (sw ^ 16),      make_uint4(o0[4], o0[5], o0[6], o0[7]));
  sts128(dst + 32 + sw,        make_uint4(o1[0], o1[1], o1[2], o1[3]));
  sts128(dst + 32 + (sw ^ 16), make_uint4(o1[4], o1[5], o1[6], o1[7]));
}

__global__ void __cluster_dims__(2, 1, 1) __launch_bounds__(NTHREADS, 1)
fused_h3_mlp_kernel(const __grid_constant__ Params P) {
  extern __shared__ __align__(1024) uint8_t smem[];
  const uint32_t sb = smem_u32(smem);
  const int tid = threadIdx.x, warp = tid >> 5, lane = tid & 31;
  const int b = blockIdx.x;
  const int rank = b & 1;
  const int pr = b >> 1, mt = pr & 15, f = (pr >> 4) + 4 * rank;
  const int jq = f & 3, kap = f >> 2;
  const uint32_t bar = sb + OFF_BAR;
  const bool has_conv = b < CONV_CTAS;

  if (warp == 0) { PROF(0); PROFG(60); }
  if (tid == 0) {
    for (int i = 0; i < 7; ++i) mbar_init(bar + 8 * (B_XFULL + i), 1);
    asm volatile("fence.mbarrier_init.release.cluster;" ::: "memory");
    fence_async_smem();
#pragma unroll
    for (int cb = 0; cb < 7; ++cb) mbar_expect_tx(bar + 8 * (B_XFULL + cb), 16384);
  } else if (tid == 32) {
    for (int i = 0; i < NSLOT; ++i) { mbar_init(bar + 8 * (B_FULL + i), 1); mbar_init(bar + 8 * (B_EMPTY + i), 2); }
    mbar_init(bar + 8 * B_HRAW, 1);
    mbar_init(bar + 8 * B_KVFULL, 1);
    mbar_init(bar + 8 * B_CONVRDY, 65);
    mbar_init(bar + 8 * B_EPIFULL, 1);
    mbar_init(bar + 8 * B_YFULL, 8);
    mbar_init(bar + 8 * B_CONVDONE, 8);
    mbar_init(bar + 8 * B_XFREE, 1);
    mbar_init(bar + 8 * B_XFULL2, 1);
    mbar_init(bar + 8 * B_HSTF, 4); mbar_init(bar + 8 * (B_HSTF + 1), 4);
    mbar_init(bar + 8 * B_HSTE, 1); mbar_init(bar + 8 * (B_HSTE + 1), 1);
    asm volatile("fence.mbarrier_init.release.cluster;" ::: "memory");
    fence_async_smem();
  } else if (tid == 64) {
    prefetch_tmap(&P.tm_xe); prefetch_tmap(&P.tm_wg); prefetch_tmap(&P.tm_wu); prefetch_tmap(&P.tm_hs); prefetch_tmap(&P.tm_hh); prefetch_tmap(&P.tm_hl);
    prefetch_tmap(&P.tm_wd); prefetch_tmap(&P.tm_out); prefetch_tmap(&P.tm_kv); prefetch_tmap(&P.tm_y); prefetch_tmap(&P.tm_yl);
  }
  __syncthreads();
  cluster_arrive_relaxed();
  cluster_wait();
  if (warp == 0) PROF(12);
  if (tid == 0) {
#pragma unroll
    for (int cb = 0; cb < 7; ++cb)
      tma2d_mc(sb + OFF_RING + 3 * SLOT_BYTES + cb * 16384 + rank * 8192, &P.tm_xe, cb * 64, mt * 128 + rank * 64, bar + 8 * (B_XFULL + cb));
    PROF(6);
  }

  if (warp < 4) {
    asm volatile("setmaxnreg.dec.sync.aligned.u32 72;");
    const int tid = fresh_tid(), warp = tid >> 5, lane = tid & 31;
    const unsigned epoch = ld_relaxed(&g_sync.epoch);
    if (warp == 0) {
      uint32_t slot = 0, use = 0;
#pragma unroll 1
      for (int n = 0; n < 30; ++n) {
        if (slot >= 3) PROD_WAIT(bar + 8 * (B_EMPTY + slot), use & 1);
        else if (use > 0) PROD_WAIT(bar + 8 * (B_EMPTY + slot), (use - 1) & 1);
        const uint32_t fb = bar + 8 * (B_FULL + slot);
        const uint32_t dst = sb + OFF_RING + slot * SLOT_BYTES;
        if (n < 16) {
          if (elect_one()) {
            mbar_expect_tx(fb, 28672);
            tma3d(dst, &P.tm_wg, wcol(n >> 2, f), f, (n & 3) * 112, fb);
            tma3d(dst + 14336, &P.tm_wu, wcol(n >> 2, f), f, (n & 3) * 112, fb);
            if (n == 3 && EXP_NOAUX == 2) { mbar_arrive(bar + 8 * B_KVFULL); if (has_conv) mbar_arrive(bar + 8 * B_HRAW); }
            if (n == 3 && EXP_NOAUX != 2) {
              const uint32_t kb = bar + 8 * B_KVFULL;
              const int r0 = b * 16;
              if (b == 0) {
                mbar_expect_tx(kb, 16 * 896 * 2);
                bulk_g2s(sb + OFF_KST + 3 * 896, P.k, 16 * 896, kb);
              } else {
                mbar_expect_tx(kb, 19 * 896 + 16 * 896);
                bulk_g2s(sb + OFF_KST, P.k + (size_t)(r0 - 3) * D_DIM, 19 * 896, kb);
              }
#pragma unroll
              for (int c = 0; c < 4; ++c)
                bulk_g2s(sb + OFF_RING + c * SLOT_BYTES + OFF_VTAIL, P.v + (size_t)(r0 + 4 * c) * D_DIM, 4 * 896, kb);
              if (has_conv) {
                const uint32_t hb = bar + 8 * B_HRAW;
                mbar_expect_tx(hb, 4 * 4096);
#pragma unroll
                for (int c = 0; c < 4; ++c)
                  bulk_g2s(sb + OFF_HC + c * HC_BYTES + HC_COPY0 + 32, P.ssm_k + (size_t)(4 * b + c) * S_LEN, 4096, hb);
              }
            }
          }
        } else {
          const int t = n - 16;
          const int kt = (int)((0xA3D962C851B740ull >> (4 * t)) & 15);
          const int k0 = kap * 896 + kt * 64;
          if (elect_one()) {
            mbar_expect_tx(fb, 32768);
            tma3d(dst + 16384, &P.tm_wd, 0, jq, k0, fb);
            tma3d(dst + 24576, &P.tm_wd, 64, jq, k0, fb);
          }
          if (t == 0 || t == 8) {
            wait_count(&g_sync.cnt_h[(mt * 2 + kap) * 32 + (t ? 16 : 0)], 4u * (epoch + 1));
            fence_async_global();
            if (t == 0) PROF(3);
          }
          __syncwarp();
          if (elect_one()) tma2d(dst, &P.tm_hl, k0, mt * 128, fb);
        }
        __syncwarp();
        PROF2(n);
        if (n == 2) PROF(1);
        if (n == 15) PROF(2);
        if (++slot == NSLOT) { slot = 0; ++use; }
      }
      PROF(4);
    } else {
      if (warp == 1) {
        if (lane == 0) mbar_expect_tx(bar + 8 * B_XFULL2, 7 * 2048);
#pragma unroll 1
        for (int p = 0; p < 4; ++p) {
#pragma unroll 1
          for (int w = 0; w < 2; ++w) {
            mbar_wait_parked(bar + 8 * (B_HSTF + w), p & 1);
            if (lane == 0) {
              if (p < 3) tma3d_store(&P.tm_hs, wcol(p, f), f, mt * 128 + w * 64, sb + OFF_HST + w * 8192);
              else       tma3d_store(&P.tm_hh, 0, 7 * f + ((f & 1) ? 0 : 6), mt * 128 + w * 64, sb + OFF_HST + w * 8192);
              bulk_commit();
              if (p < 3) {
                bulk_wait_read0();
                mbar_arrive(bar + 8 * (B_HSTE + w));
                if (p == 1 && w == 1) {
                  bulk_wait0();
                  red_relaxed_add(&g_sync.cnt_h[(mt * 2 + kap) * 32], 1);
                }
              }
            }
            __syncwarp();
          }
        }
        PROF(8);
        const uint32_t eb = bar + 8 * B_EPIFULL;
        if (lane == 0) {
          bulk_wait0();
          red_relaxed_add(&g_sync.cnt_h[(mt * 2 + kap) * 32 + 16], 1);
          mbar_expect_tx(eb, 16384 + 14336);
          tma2d(sb + OFF_HST, &P.tm_xe, jq * 112, mt * 128 + kap * 64, eb);
          tma2d(sb + OFF_HST + 8192, &P.tm_xe, jq * 112 + 64, mt * 128 + kap * 64, eb);
        }
        __syncwarp();
        if (has_conv) {
          mbar_wait_parked(bar + 8 * B_YFULL, 0);
          if (lane == 0) {
#pragma unroll
            for (int i = 0; i < 8; ++i)
              tma3d_store(&P.tm_y, 0, 4 * b + (i >> 1), 16 * (i & 1), sb + OFF_HC + (i >> 1) * HC_BYTES + (i & 1) * 4096);
            bulk_commit();
            bulk_wait0();
            red_relaxed_add(&g_sync.cnt_y[(b / 28) * 32], 1);
          }
          __syncwarp();
        }
        if (lane == 0) mbar_arrive_cta(bar + 8 * B_XFREE, rank ^ 1);
        PROF(10);
        mbar_wait_parked(bar + 8 * B_CONVDONE, 0);
        wait_count(&g_sync.cnt_y[jq * 32], 28u * (epoch + 1));
        fence_async_global();
        __syncwarp();
        if (lane == 0) { tma2d(sb + OFF_C, &P.tm_yl, 0, (mt * 2 + kap) * D_DIM + jq * 112, eb); prefetch_tmap(&P.tm_out); }
        PROF(11);
      } else {
        const int at = tid - 64;
        uint4 wsh[4];
#pragma unroll
        for (int i = 0; i < 4; ++i) {
          const int cp = at + 64 * i;
          wsh[i] = cp < 224 ? __ldg(reinterpret_cast<const uint4*>(P.shift_k) + cp) : make_uint4(0, 0, 0, 0);
        }
        mbar_wait_parked(bar + 8 * B_KVFULL, 0);
        if (warp == 3) PROF(7);
        if (b == 0) {
          for (int i = at; i < 3 * 896 / 16; i += 64) sts128(sb + OFF_KST + i * 16, make_uint4(0, 0, 0, 0));
          bar_sync(4, 64);
        }
#pragma unroll
        for (int i = 0; i < 4; ++i) {
          const int cp = at + 64 * i;
          if (cp < 224 && !EXP_NOAUX) kv_prepass(sb + OFF_KST, sb + OFF_RING + OFF_VTAIL, sb + OFF_HC, wsh[i], b, cp);
        }
        fence_async_smem();
        bar_sync(4, 64);
        if (at == 0) {
#pragma unroll
          for (int c = 0; c < 4; ++c) tma2d_store(&P.tm_kv, 16 * b, 112 * c, sb + OFF_HC + c * HC_BYTES);
          bulk_commit();
          bulk_wait_read0();
        }
        bar_sync(4, 64);
        if (at == 0) { bulk_wait0(); red_relaxed_add(&g_sync.cnt_kv, 1); }
        __syncwarp();
        if (warp == 2) PROF(14);
        if (has_conv) {
          mbar_wait_parked(bar + 8 * B_HRAW, 0);
#pragma unroll 1
          for (int c = (warp == 2 ? 2 : 0); c < (EXP_NOAUX ? 0 : (warp == 2 ? 4 : 2)); ++c) {
            const uint32_t hb = sb + OFF_HC + c * HC_BYTES;
            uint4 v[8];
#pragma unroll
            for (int i = 0; i < 8; ++i) v[i] = lds128(hb + HC_COPY0 + 32 + (i * 32 + lane) * 16);
#pragma unroll
            for (int i = 0; i < 8; ++i) {
              uint32_t nx = __shfl_down_sync(0xffffffffu, v[i].x, 1);
              const uint32_t first_next = __shfl_sync(0xffffffffu, v[i < 7 ? i + 1 : 7].x, 0);
              if (lane == 31) nx = i < 7 ? first_next : 0u;
              sts128(hb + 32 + (i * 32 + lane) * 16, make_uint4(__byte_perm(v[i].x, v[i].y, 0x5432), __byte_perm(v[i].y, v[i].z, 0x5432),
                                                                 __byte_perm(v[i].z, v[i].w, 0x5432), __byte_perm(v[i].w, nx, 0x5432)));
            }
            if (lane == 0) {
              sts128(hb + HC_COPY0, make_uint4(0, 0, 0, 0));
              sts128(hb + HC_COPY0 + 16, make_uint4(0, 0, 0, 0));
              sts128(hb, make_uint4(0, 0, 0, 0));
              sts128(hb + 16, make_uint4(0, 0, 0, v[0].x << 16));
            }
          }
          if (warp == 2) PROF(15);
          sts128(sb + OFF_U + (at >> 4) * U_BYTES + (at & 15) * 16, make_uint4(0, 0, 0, 0));
          if (warp == 2) {
            wait_count(&g_sync.cnt_kv, (unsigned)NCTA * (epoch + 1));
            fence_async_global();
            __syncwarp();
            if (lane == 0) {
              const uint32_t cb = bar + 8 * B_CONVRDY;
              mbar_expect_tx(cb, 4 * 4096);
#pragma unroll
              for (int c = 0; c < 4; ++c) bulk_g2s(sb + OFF_U + c * U_BYTES + 256, g_kvT + (size_t)(4 * b + c) * S_LEN, 4096, cb);
            }
            PROF(5);
          }
          mbar_arrive(bar + 8 * B_CONVRDY);
        }
      }
    }
    cluster_arrive_relaxed();
    cluster_wait();
  } else {
    asm volatile("setmaxnreg.inc.sync.aligned.u32 216;");
    const int tid = fresh_tid(), warp = tid >> 5, lane = tid & 31;
    const int cw = (warp >> 2) - 1, wq = warp & 3;
    const int g = lane >> 2, t = lane & 3;
    const bool leader = (tid & 127) == 0;
    const int pb = (warp & 3) == 0 ? (cw == 0 ? 16 : 32) : -1;
    (void)pb;
    const unsigned epoch = ld_relaxed(&g_sync.epoch);
    uint32_t dv = 0;
    if (has_conv) dv = __bfloat16_as_ushort(__ldg(P.ssm_D + 4 * b + ((warp - 4) >> 1)));

    uint32_t xa[28][4];
    uint32_t m2[2], rh2[2], rl2[2];
    {
      float cs[2][4] = {}, q0[2][4] = {}, q1[2][4] = {};
      const uint32_t lrow = cw * 64 + wq * 16 + (lane & 7) + ((lane >> 3) & 1) * 8;
      const uint32_t lch = lane >> 4;
#pragma unroll
      for (int cb = 0; cb < 7; ++cb) {
        mbar_wait(bar + 8 * (B_XFULL + cb), 0);
        if (warp == 4) PROF2(112 + cb);
        const uint32_t boxo = cb < 4 ? OFF_RING + 3 * SLOT_BYTES + cb * 16384 : (cb == 4 ? OFF_HST : OFF_C + (cb - 5) * 16384);
        const uint32_t base = sb + boxo + lrow * 128;
#pragma unroll
        for (int c = 0; c < 4; ++c) {
          const int kk = 4 * cb + c;
          ldsm_x4(xa[kk], base + (((2 * c + lch) ^ (lrow & 7)) << 4));
          hmma(cs[kk & 1], xa[kk][0], xa[kk][1], xa[kk][2], xa[kk][3], 0x3F803F80u, 0x3F803F80u);
          hmma(q0[kk & 1], xa[kk][0], xa[kk][1], xa[kk][2], xa[kk][3], xa[kk][0], xa[kk][2]);
          hmma(q1[kk & 1], xa[kk][0], xa[kk][1], xa[kk][2], xa[kk][3], xa[kk][1], xa[kk][3]);
        }
      }
      if (pb >= 0) PROF(pb + 0);
      bar_sync(1 + cw, 128);
      release_slot(sb, 3, leader);
      release_slot(sb, 4, leader);
      const int src = (lane & ~3) | (g >> 1);
      const float sqa = __shfl_sync(0xffffffffu, (g & 1) ? q0[0][1] + q0[1][1] : q0[0][0] + q0[1][0], src);
      const float sqb = __shfl_sync(0xffffffffu, (g & 1) ? q1[0][3] + q1[1][3] : q1[0][2] + q1[1][2], src);
#pragma unroll
      for (int r = 0; r < 2; ++r) {
        const float sum = cs[0][2 * r] + cs[1][2 * r];
        const float sq = r ? sqb : sqa;
        const float mean = sum * (1.0f / D_DIM);
        const float var = fmaxf(sq * (1.0f / D_DIM) - mean * mean, 0.0f);
        const float den = bf16_round(sqrt_approx(bf16_round(bf16_round(var) + 1e-5f)));
        const float rinv = rcp_approx(den);
        const float rh = bf16_round(rinv);
        m2[r] = dup_bf16(mean); rh2[r] = dup_bf16(rh); rl2[r] = dup_bf16(rinv - rh);
        if (t == 0) sts64(sb + OFF_STAT + (cw * 64 + wq * 16 + g + 8 * r) * 8, (m2[r] & 0xffffu) | (rh2[r] << 16), rl2[r] & 0xffffu);
      }
    }
    if (pb >= 0) PROF(pb + 1);

    Ring rg{0, 0};
    {
      const uint32_t srow = wq * 16 + (lane & 7) + ((lane >> 3) & 1) * 8;
      const uint32_t saddr = sb + OFF_HST + cw * 8192 + srow * 128;
      float acc[64], ag[16], au[16];
      gemm1_pass<0>(acc, ag, au, xa, m2, rh2, rl2, rg, sb, leader, cw, wq == 0 ? 32 + cw * 32 : -1000, 0, lane);
      gemm1_stage_h<8>(acc, acc + 32, saddr, srow, lane, 0);
      if (pb >= 0) PROF(pb + 2);
#pragma unroll 1
      for (int p = 1; p < 3; ++p) {
        gemm1_pass<1>(acc, ag, au, xa, m2, rh2, rl2, rg, sb, leader, cw, wq == 0 ? 32 + cw * 32 + 8 * p : -1000, 0, lane);
        mbar_wait(bar + 8 * (B_HSTE + cw), (p - 1) & 1);
        gemm1_stage_h<8>(acc, acc + 32, saddr, srow, lane, 0);
        if (pb >= 0) PROF(pb + 2 + p);
      }
      gemm1_pass<2>(acc, ag, au, xa, m2, rh2, rl2, rg, sb, leader, cw, wq == 0 ? 32 + cw * 32 + 24 : -1000, (f & 1) * 64, lane);
      mbar_wait(bar + 8 * (B_HSTE + cw), 0);
      gemm1_stage_h<4>(ag, au, saddr, srow, lane, 0);
      fence_async_smem();
      __syncwarp();
      if (lane == 0) mbar_arrive(bar + 8 * (B_HSTF + cw));
    }
    if (pb >= 0) PROF(pb + 5);

    const int cwarp = warp - 4, cc_ = cwarp >> 1, hh = cwarp & 1;
    const uint32_t ub = sb + OFF_U + cc_ * U_BYTES;
    const uint32_t hb = sb + OFF_HC + cc_ * HC_BYTES;
    float cacc[16][4];
#pragma unroll
    for (int i = 0; i < 16; ++i) { cacc[i][0] = cacc[i][1] = cacc[i][2] = cacc[i][3] = 0.f; }
    const uint32_t abase = hb + ((g & 1) ? HC_COPY0 + 4 * (((1 + g) >> 1) + t) : 4 * ((g >> 1) + t));
    float acc2[56];
    uint32_t dfrag = 0;
    if (has_conv) {
      const int e = 7 - g - 2 * t;
      dfrag = (e == 0) ? dv : (e == 1 ? dv << 16 : 0u);
      mbar_wait(bar + 8 * B_CONVRDY, 0);
    }
    if (pb >= 0) PROF(pb + 6);
    int r = 4 * hh, st = 0;
#pragma unroll 1
    for (int seg = 0; seg < 3; ++seg) {
      if (has_conv) {
        const int rend = seg == 2 ? 4 * hh + 4 : r + (seg == 0 ? SCHED_NR0 : SCHED_NR1);
#pragma unroll 1
        for (; r < rend; ++r) {
          if (warp == 4) PROF2(124 + r);
          const uint32_t R = 8 + 8 * (lane >> 4) + (lane & 7) - r;
          const uint32_t baddr = ub + 32 * R + 16 * (((lane >> 3) & 1) ^ ((R >> 2) & 1));
          const uint32_t aaddr = abase + 32 * r;
          uint32_t bf[16][2];
#pragma unroll
          for (int jp = 7; jp >= 0; --jp) ldsm_x4(bf[2 * jp][0], bf[2 * jp][1], bf[2 * jp + 1][0], bf[2 * jp + 1][1], baddr + 512 * jp);
          if (r == 0) {
#pragma unroll
            for (int tau = 15; tau >= 0; --tau) hmma(cacc[tau], 0u, dfrag, dfrag, 0u, bf[tau][0], bf[tau][1]);
          }
          uint32_t aL[4], aS[4];
          aL[0] = lds32v(aaddr); aL[1] = lds32v(aaddr + 16); aL[3] = lds32v(aaddr + 32);
          aS[0] = lds32v(aaddr + 256 * 15); aS[1] = lds32v(aaddr + 256 * 15 + 16); aS[3] = lds32v(aaddr + 256 * 15 + 32);
          aL[2] = lds32v(aaddr + 16); aS[2] = lds32v(aaddr + 256 * 15 + 16);
#pragma unroll
          for (int q = 0; q < 8; ++q) {
            const int q2 = 15 - q;
            uint32_t nL[4] = {0, 0, 0, 0}, nS[4] = {0, 0, 0, 0};
            if (q < 7) {
              nL[0] = lds32v(aaddr + 256 * (q + 1)); nL[1] = lds32v(aaddr + 256 * (q + 1) + 16); nL[3] = lds32v(aaddr + 256 * (q + 1) + 32);
              nS[0] = lds32v(aaddr + 256 * (q2 - 1)); nS[1] = lds32v(aaddr + 256 * (q2 - 1) + 16); nS[3] = lds32v(aaddr + 256 * (q2 - 1) + 32);
              nL[2] = lds32v(aaddr + 256 * (q + 1) + 16); nS[2] = lds32v(aaddr + 256 * (q2 - 1) + 16);
            }
#pragma unroll
            for (int tau = 15; tau >= 8; --tau) hmma(cacc[tau], aL[0], aL[1], aL[2], aL[3], bf[tau - q][0], bf[tau - q][1]);
#pragma unroll
            for (int tau = 15; tau >= q2; --tau) hmma(cacc[tau], aS[0], aS[1], aS[2], aS[3], bf[tau - q2][0], bf[tau - q2][1]);
#pragma unroll
            for (int tau = 7; tau >= q; --tau) hmma(cacc[tau], aL[0], aL[1], aL[2], aL[3], bf[tau - q][0], bf[tau - q][1]);
#pragma unroll
            for (int i = 0; i < 4; ++i) { aL[i] = nL[i]; aS[i] = nS[i]; }
          }
        }
        if (seg == SCHED_FSEG) {
          if (pb >= 0) PROF(pb + 7);
          bar_sync(5 + cc_, 64);
          const uint32_t oth = hb + (1 - hh) * 4096 + lane * 16;
#pragma unroll
          for (int i = 0; i < 8; ++i)
            sts128(oth + i * 512, make_uint4(__float_as_uint(hh ? cacc[i][0] : cacc[8 + i][0]), __float_as_uint(hh ? cacc[i][1] : cacc[8 + i][1]),
                                             __float_as_uint(hh ? cacc[i][2] : cacc[8 + i][2]), __float_as_uint(hh ? cacc[i][3] : cacc[8 + i][3])));
          bar_sync(5 + cc_, 64);
          const uint32_t area = hb + hh * 4096;
          uint32_t yp[8][2];
#pragma unroll
          for (int i = 0; i < 8; ++i) {
            const uint4 v = lds128(area + i * 512 + lane * 16);
            yp[i][0] = (pack_bf16((hh ? cacc[8 + i][0] : cacc[i][0]) + __uint_as_float(v.x), (hh ? cacc[8 + i][1] : cacc[i][1]) + __uint_as_float(v.y)));
            yp[i][1] = (pack_bf16((hh ? cacc[8 + i][2] : cacc[i][2]) + __uint_as_float(v.z), (hh ? cacc[8 + i][3] : cacc[i][3]) + __uint_as_float(v.w)));
          }
          __syncwarp();
#pragma unroll
          for (int i = 0; i < 8; i += 2) {
            const uint32_t bl = 8 * (i + (lane >> 4)) + (lane & 7);
            stsm_x4_t(area + 32 * bl + 16 * (((lane >> 3) & 1) ^ ((bl >> 2) & 1)), yp[i][0], yp[i][1], yp[i + 1][0], yp[i + 1][1]);
          }
          fence_async_smem();
          __syncwarp();
          if (lane == 0) mbar_arrive(bar + 8 * B_YFULL);
        }
      }
      if (seg < 2) {
        if (warp == 4) PROF(56 + seg);
        bar_sync(3, 256);
        gemm2_chunk(acc2, st, st + (seg == 0 ? SCHED_NS0 : SCHED_NS1), rg, sb, leader, cw);
        if (pb >= 0 && seg < 1) PROF(pb + 9);
        if (warp == 4 && seg == 1) PROF(59);
      }
    }
    __syncwarp();
    if (lane == 0) mbar_arrive(bar + 8 * B_CONVDONE);
    if (pb >= 0) PROF(pb + 8);
    const int t128 = tid & 127;
    if (cw == kap) cluster_arrive_relaxed();
    if (XSEND_FIRST) { if (cw == kap) bar_sync(3, 256); } else bar_sync(3, 256);
    {
      constexpr int NLAST = 14 - SCHED_NS0 - SCHED_NS1;
#pragma unroll
      for (int i = 0; i < NLAST; ++i) {
        mbar_wait(bar + 8 * (B_FULL + rg.slot), rg.phase);
        const uint32_t base = sb + OFF_RING + rg.slot * SLOT_BYTES;
        const uint64_t da = make_desc(base + cw * 8192, 16, 1024);
        const uint64_t db = make_desc(base + 16384, 8192, 1024);
        wg_fence();
#pragma unroll
        for (int kk = 0; kk < 4; ++kk) wgmma_ss_n112(acc2, da + kk * 2, db + kk * 128, 1);
        wg_commit();
        rg.next();
      }
      if (XSEND_FIRST && cw != kap) asm volatile("bar.arrive 3, 256;" ::: "memory");
      wg_wait<0>();
    }
    if (pb >= 0) PROF(pb + 10);

    if (cw != kap) {
      mbar_wait(bar + 8 * B_XFREE, 0);
      const uint32_t dst = mapa(sb + OFF_HC + t128 * 16, rank ^ 1), rb = mapa(bar + 8 * B_XFULL2, rank ^ 1);
#pragma unroll
      for (int q = 0; q < 7; ++q)
        st_async_v4(dst + q * 2048, pack_bf16(acc2[8 * q], acc2[8 * q + 1]), pack_bf16(acc2[8 * q + 2], acc2[8 * q + 3]),
                    pack_bf16(acc2[8 * q + 4], acc2[8 * q + 5]), pack_bf16(acc2[8 * q + 6], acc2[8 * q + 7]), rb);
      cluster_arrive_relaxed();
      if (pb >= 0) PROF(pb + 11);
    } else {
      if (pb >= 0) PROF(52);
      mbar_wait(bar + 8 * B_EPIFULL, 0);
      if (pb >= 0) PROF(53);
      uint32_t o1[14][2];
      {
        uint32_t em2[2], erh2[2], erl2[2];
#pragma unroll
        for (int rr = 0; rr < 2; ++rr) {
          uint32_t s0, s1;
          asm volatile("ld.shared.v2.u32 {%0,%1}, [%2];" : "=r"(s0), "=r"(s1) : "r"(sb + OFF_STAT + (kap * 64 + wq * 16 + g + 8 * rr) * 8) : "memory");
          em2[rr] = __byte_perm(s0, 0, 0x1010); erh2[rr] = __byte_perm(s0, 0, 0x3232); erl2[rr] = __byte_perm(s1, 0, 0x1010);
        }
        const uint32_t xrow = wq * 16 + (lane & 7) + ((lane >> 3) & 1) * 8;
        uint32_t x[7][4], yf[7][4];
#pragma unroll
        for (int jp = 0; jp < 7; ++jp) {
          const int jn = 2 * jp;
          const uint32_t chunk = (jn & 7) + (lane >> 4);
          ldsm_x4(x[jp][0], x[jp][1], x[jp][2], x[jp][3], sb + OFF_HST + (jn >> 3) * 8192 + xrow * 128 + ((chunk ^ (xrow & 7)) << 4));
          const uint32_t chrow = 8 * (jn + (lane >> 4)) + (lane & 7);
          const uint32_t tc = (2 * wq + ((lane >> 3) & 1)) ^ kap;
          ldsm_x4_t(yf[jp][0], yf[jp][1], yf[jp][2], yf[jp][3], sb + OFF_C + chrow * 128 + ((tc ^ (chrow & 7)) << 4));
        }
#pragma unroll
        for (int jp = 0; jp < 7; ++jp) {
#pragma unroll
          for (int i = 0; i < 4; ++i) {
            const int rr = i & 1;
            const uint32_t d = bsub2(x[jp][i], em2[rr]);
            const uint32_t xn = bfma2(d, erh2[rr], bmul2(d, erl2[rr]));
            o1[2 * jp + (i >> 1)][rr] = badd2(x[jp][i], bmul2(xn, yf[jp][i]));
          }
        }
      }
      if (pb >= 0) PROF(pb + 13);
      mbar_wait(bar + 8 * B_XFULL2, 0);
      uint4 pv[7];
#pragma unroll
      for (int q = 0; q < 7; ++q) pv[q] = lds128(sb + OFF_HC + q * 2048 + t128 * 16);
      if (pb >= 0) PROF(55);
      const uint32_t xrow2 = wq * 16 + (lane & 7) + ((lane >> 3) & 1) * 8;
#pragma unroll
      for (int jn = 0; jn < 14; jn += 2) {
        const uint32_t pw[4] = {pv[jn >> 1].x, pv[jn >> 1].y, pv[jn >> 1].z, pv[jn >> 1].w};
        uint32_t o[4];
#pragma unroll
        for (int i = 0; i < 4; ++i) {
          const int q = jn + (i >> 1), rr = i & 1;
          o[i] = badd2(o1[q][rr], pack_bf16(acc2[4 * q + 2 * rr] + __uint_as_float(pw[i] << 16),
                                            acc2[4 * q + 2 * rr + 1] + __uint_as_float(pw[i] & 0xffff0000u)));
        }
        const uint32_t chunk = (jn & 7) + (lane >> 4);
        stsm_x4(sb + OFF_HST + (jn >> 3) * 8192 + xrow2 * 128 + ((chunk ^ (xrow2 & 7)) << 4), o[0], o[1], o[2], o[3]);
      }
      if (pb >= 0) PROF(54);
      fence_async_smem();
      __syncwarp();
      if (lane == 0) {
        tma3d_store(&P.tm_out, 0, jq, mt * 128 + kap * 64 + wq * 16, sb + OFF_HST + wq * 2048);
        tma3d_store(&P.tm_out, 64, jq, mt * 128 + kap * 64 + wq * 16, sb + OFF_HST + 8192 + wq * 2048);
        bulk_commit();
        bulk_wait_read0();
        if (b == 0 && wq == 0) *(volatile unsigned*)&g_sync.epoch = epoch + 1;
      }
      if (pb >= 0) PROF(pb + 12);
    }
    cluster_wait();
    if (warp == 4) { PROF(48); PROFG(61); }
  }
}

typedef CUresult (*EncodeFn)(CUtensorMap*, CUtensorMapDataType, cuuint32_t, void*, const cuuint64_t*, const cuuint64_t*,
                             const cuuint32_t*, const cuuint32_t*, CUtensorMapInterleave, CUtensorMapSwizzle,
                             CUtensorMapL2promotion, CUtensorMapFloatOOBfill);

void encode(EncodeFn fn, CUtensorMap* m, const void* base, int rank, const cuuint64_t* dims, const cuuint64_t* strides, const cuuint32_t* box,
            CUtensorMapSwizzle swz = CU_TENSOR_MAP_SWIZZLE_128B) {
  cuuint32_t es[3] = {1, 1, 1};
  fn(m, CU_TENSOR_MAP_DATA_TYPE_BFLOAT16, (cuuint32_t)rank, const_cast<void*>(base), dims, strides, box, es,
     CU_TENSOR_MAP_INTERLEAVE_NONE, swz, (CUtensorMapL2promotion)L2PROMO, CU_TENSOR_MAP_FLOAT_OOB_FILL_NONE);
}
void encode2(EncodeFn fn, CUtensorMap* m, const void* base, uint64_t cols, uint64_t rows, uint32_t bc, uint32_t br) {
  cuuint64_t d[2] = {cols, rows}; cuuint64_t s[1] = {cols * 2}; cuuint32_t bx[2] = {bc, br};
  encode(fn, m, base, 2, d, s, bx);
}
void encode3(EncodeFn fn, CUtensorMap* m, const void* base, uint64_t w, uint64_t nslice, uint64_t rows, uint32_t bc, uint32_t br) {
  cuuint64_t d[3] = {w, nslice, rows}; cuuint64_t s[2] = {w * 2, w * nslice * 2}; cuuint32_t bx[3] = {bc, 1, br};
  encode(fn, m, base, 3, d, s, bx);
}

}

extern "C" void kernel_launch(void* const* d_in, const int* in_sizes, int n_in, void* d_out, int out_size) {
  (void)in_sizes; (void)n_in; (void)out_size;
  static EncodeFn fn = nullptr;
  if (!fn) {
    void* p = nullptr;
    cudaDriverEntryPointQueryResult qr;
    cudaGetDriverEntryPoint("cuTensorMapEncodeTiled", &p, cudaEnableDefault, &qr);
    fn = (EncodeFn)p;
    cudaFuncSetAttribute(fused_h3_mlp_kernel, cudaFuncAttributeMaxDynamicSharedMemorySize, SMEM_BYTES);
  }
  void *h, *kv, *y2;
  cudaGetSymbolAddress(&y2, g_y2T);
  cudaGetSymbolAddress(&kv, g_kvT);
  cudaGetSymbolAddress(&h, g_h);
  Params P;
  const void* x = d_in[0];
  encode3(fn, &P.tm_wg, d_in[7], 224, 8, D_DIM, 64, 112);
  encode3(fn, &P.tm_wu, d_in[8], 224, 8, D_DIM, 64, 112);
  encode3(fn, &P.tm_hs, h, 224, 8, S_LEN, 64, 64);
  encode3(fn, &P.tm_hh, h, 32, 56, S_LEN, 64, 64);
  encode2(fn, &P.tm_hl, h, F_DIM, S_LEN, 64, 128);
  encode3(fn, &P.tm_wd, d_in[9], 112, 4, F_DIM, 64, 64);
  encode2(fn, &P.tm_xe, x, D_DIM, S_LEN, 64, 64);
  {
    cuuint64_t d[2] = {S_LEN, D_DIM}; cuuint64_t st[1] = {S_LEN * 2}; cuuint32_t bx[2] = {16, 112};
    encode(fn, &P.tm_kv, kv, 2, d, st, bx, CU_TENSOR_MAP_SWIZZLE_NONE);
  }
  {
    cuuint64_t d[3] = {64, D_DIM, 32}; cuuint64_t st[2] = {128, (cuuint64_t)D_DIM * 128}; cuuint32_t bx[3] = {64, 1, 16};
    encode(fn, &P.tm_y, y2, 3, d, st, bx, CU_TENSOR_MAP_SWIZZLE_NONE);
  }
  encode2(fn, &P.tm_yl, y2, 64, 32 * D_DIM, 64, 112);
  encode3(fn, &P.tm_out, d_out, 112, 4, S_LEN, 64, 16);
  P.k = (const __nv_bfloat16*)d_in[1];
  P.v = (const __nv_bfloat16*)d_in[2];
  P.shift_k = (const __nv_bfloat16*)d_in[3];
  P.ssm_k = (const __nv_bfloat16*)d_in[4];
  P.ssm_D = (const __nv_bfloat16*)d_in[5];
  P.wg = (const __nv_bfloat16*)d_in[7];
  P.wu = (const __nv_bfloat16*)d_in[8];
  P.wd = (const __nv_bfloat16*)d_in[9];
  P.out = (__nv_bfloat16*)d_out;
  fused_h3_mlp_kernel<<<NCTA, NTHREADS, SMEM_BYTES>>>(P);
}
```

```cpp
#include <cuda_runtime.h>
#include <cuda_bf16.h>
#include <cuda.h>
#include <stdint.h>

namespace {

constexpr int S_LEN = 2048;
constexpr int D_DIM = 448;
constexpr int F_DIM = 1792;
constexpr int NCTA  = 128;
constexpr int NTHREADS = 384;
constexpr int CONV_CTAS = 112;

constexpr uint32_t SLOT_BYTES = 32768;
constexpr int      NSLOT      = 5;
constexpr uint32_t OFF_RING = 0;
constexpr uint32_t OFF_HST  = NSLOT * SLOT_BYTES;
constexpr uint32_t OFF_C    = OFF_HST + 16384;
constexpr uint32_t U_BYTES  = 4352;
constexpr uint32_t HC_BYTES = 8320;
constexpr uint32_t HC_COPY0 = 4160;
constexpr uint32_t OFF_U    = OFF_C;
constexpr uint32_t OFF_HC   = OFF_C + 4 * U_BYTES;
constexpr uint32_t OFF_KST  = OFF_U;
constexpr uint32_t OFF_VTAIL = 28672;
constexpr uint32_t OFF_MISC = OFF_HC + 4 * HC_BYTES;
constexpr uint32_t OFF_BAR  = OFF_MISC;
constexpr uint32_t OFF_EPOCH = OFF_MISC + 384;
constexpr uint32_t OFF_STAT = OFF_MISC + 512;
constexpr uint32_t SMEM_BYTES = OFF_STAT + 512;
static_assert(SMEM_BYTES <= 232448, "smem");

constexpr int B_FULL = 0, B_EMPTY = 5, B_XFULL = 10, B_HRAW = 17, B_CONVRDY = 18, B_EPIFULL = 19,
              B_KVFULL = 20, B_HSTF = 21, B_HSTE = 23, B_YFULL = 25, B_CONVDONE = 26, B_XFREE = 27, B_XFULL2 = 28, B_STAT = 29, B_KVDONE = 30;

struct alignas(64) Params {
  CUtensorMap tm_wg;
  CUtensorMap tm_wu;
  CUtensorMap tm_wgh;
  CUtensorMap tm_wuh;
  CUtensorMap tm_hs;
  CUtensorMap tm_hh;
  CUtensorMap tm_hl;
  CUtensorMap tm_wd;
  CUtensorMap tm_xe;
  CUtensorMap tm_y;
  CUtensorMap tm_yl;
  CUtensorMap tm_kv;
  CUtensorMap tm_out;
  const __nv_bfloat16* k;
  const __nv_bfloat16* v;
  const __nv_bfloat16* shift_k;
  const __nv_bfloat16* ssm_k;
  const __nv_bfloat16* ssm_D;
};

__device__ __align__(1024) __nv_bfloat16 g_h[S_LEN * F_DIM];
__device__ __align__(1024) __nv_bfloat16 g_kvT[D_DIM * S_LEN];
__device__ __align__(1024) __nv_bfloat16 g_y2T[D_DIM * S_LEN];
struct Sync {
  unsigned epoch;      unsigned pad0[31];
  unsigned cnt_kv;     unsigned pad1[31];
  unsigned cnt_h[32 * 32];
  unsigned cnt_y[4 * 32];
};
__device__ __align__(1024) Sync g_sync;

__device__ __forceinline__ int fresh_tid() { int t; asm volatile("mov.u32 %0, %%tid.x;" : "=r"(t)); return t; }
__device__ __forceinline__ unsigned late(unsigned v) { asm volatile("" : "+r"(v)); return v; }
__device__ __forceinline__ uint32_t smem_u32(const void* p) { return (uint32_t)__cvta_generic_to_shared(p); }
__device__ __forceinline__ void mbar_init(uint32_t a, uint32_t c) { asm volatile("mbarrier.init.shared::cta.b64 [%0], %1;" ::"r"(a), "r"(c)); }
__device__ __forceinline__ void mbar_expect_tx(uint32_t a, uint32_t bytes) {
  asm volatile("mbarrier.arrive.expect_tx.shared::cta.b64 _, [%0], %1;" ::"r"(a), "r"(bytes) : "memory");
}
__device__ __forceinline__ void mbar_arrive(uint32_t a) { asm volatile("mbarrier.arrive.shared::cta.b64 _, [%0];" ::"r"(a) : "memory"); }
__device__ __forceinline__ void mbar_arrive_cta(uint32_t a, uint32_t cta) {
  asm volatile("{\n.reg .b32 r;\nmapa.shared::cluster.u32 r, %0, %1;\nmbarrier.arrive.shared::cluster.b64 _, [r];\n}" ::"r"(a), "r"(cta) : "memory");
}
__device__ __forceinline__ bool mbar_try(uint32_t a, uint32_t ph) {
  uint32_t ok;
  asm volatile("{\n.reg .pred p;\nmbarrier.try_wait.parity.shared::cta.b64 p, [%1], %2;\nselp.u32 %0, 1, 0, p;\n}" : "=r"(ok) : "r"(a), "r"(ph) : "memory");
  return ok != 0;
}
constexpr uint32_t WAIT_HINT_NS = 2000u;
constexpr uint32_t SPIN_LIMIT = 1u << 15;
constexpr uint32_t SPIN_LIMIT_FAST = 1u << 18;
__device__ __forceinline__ void mbar_wait(uint32_t a, uint32_t ph) {
  if (mbar_try(a, ph)) return;
  uint32_t it = 0;
  while (!mbar_try(a, ph)) { if (++it > SPIN_LIMIT_FAST) break; }
}
__device__ __forceinline__ void mbar_wait_parked(uint32_t a, uint32_t ph) {
  uint32_t it = 0, ok;
  do {
    asm volatile("{\n.reg .pred p;\nmbarrier.try_wait.parity.shared::cta.b64 p, [%1], %2, %3;\nselp.u32 %0, 1, 0, p;\n}"
                 : "=r"(ok) : "r"(a), "r"(ph), "r"(WAIT_HINT_NS) : "memory");
  } while (!ok && ++it <= SPIN_LIMIT);
}
__device__ __forceinline__ unsigned ld_acquire(const unsigned* p) {
  unsigned v; asm volatile("ld.acquire.gpu.global.u32 %0, [%1];" : "=r"(v) : "l"(p) : "memory"); return v;
}
__device__ __forceinline__ unsigned ld_relaxed(const unsigned* p) {
  unsigned v; asm volatile("ld.relaxed.gpu.global.u32 %0, [%1];" : "=r"(v) : "l"(p) : "memory"); return v;
}
__device__ __forceinline__ void wait_count(const unsigned* p, unsigned target) {
  uint32_t it = 0;
  while ((int)(ld_acquire(p) - target) < 0) { if (++it > SPIN_LIMIT) break; }
}
__device__ __forceinline__ bool elect_one() {
  uint32_t p;
  asm volatile("{\n.reg .pred P;\nelect.sync _|P, 0xffffffff;\nselp.u32 %0, 1, 0, P;\n}" : "=r"(p));
  return p != 0;
}
__device__ __forceinline__ void bar_sync(int id, int n) { asm volatile("bar.sync %0, %1;" ::"r"(id), "r"(n) : "memory"); }
__device__ __forceinline__ void fence_async_smem() { asm volatile("fence.proxy.async.shared::cta;" ::: "memory"); }
__device__ __forceinline__ void fence_async_global() { asm volatile("fence.proxy.async.global;" ::: "memory"); }
__device__ __forceinline__ void cluster_arrive_relaxed() { asm volatile("barrier.cluster.arrive.relaxed.aligned;" ::: "memory"); }
__device__ __forceinline__ void cluster_wait() { asm volatile("barrier.cluster.wait.acquire.aligned;" ::: "memory"); }

__device__ __forceinline__ void tma2d(uint32_t dst, const CUtensorMap* m, int c0, int c1, uint32_t bar) {
  asm volatile("cp.async.bulk.tensor.2d.shared::cluster.global.mbarrier::complete_tx::bytes [%0], [%1, {%3, %4}], [%2];"
               ::"r"(dst), "l"(m), "r"(bar), "r"(c0), "r"(c1) : "memory");
}
__device__ __forceinline__ void tma2d_mc(uint32_t dst, const CUtensorMap* m, int c0, int c1, uint32_t bar) {
  asm volatile("cp.async.bulk.tensor.2d.shared::cluster.global.mbarrier::complete_tx::bytes.multicast::cluster [%0], [%1, {%3, %4}], [%2], %5;"
               ::"r"(dst), "l"(m), "r"(bar), "r"(c0), "r"(c1), "h"((uint16_t)3) : "memory");
}
__device__ __forceinline__ void tma3d(uint32_t dst, const CUtensorMap* m, int c0, int c1, int c2, uint32_t bar) {
  asm volatile("cp.async.bulk.tensor.3d.shared::cluster.global.mbarrier::complete_tx::bytes [%0], [%1, {%3, %4, %5}], [%2];"
               ::"r"(dst), "l"(m), "r"(bar), "r"(c0), "r"(c1), "r"(c2) : "memory");
}
__device__ __forceinline__ uint32_t mapa(uint32_t a, uint32_t cta) { uint32_t r; asm("mapa.shared::cluster.u32 %0, %1, %2;" : "=r"(r) : "r"(a), "r"(cta)); return r; }
__device__ __forceinline__ void st_async_v4(uint32_t dst, uint32_t a, uint32_t b, uint32_t c, uint32_t d, uint32_t bar) {
  asm volatile("st.async.weak.shared::cluster.mbarrier::complete_tx::bytes.v4.b32 [%0], {%1,%2,%3,%4}, [%5];"
               ::"r"(dst), "r"(a), "r"(b), "r"(c), "r"(d), "r"(bar) : "memory");
}
__device__ __forceinline__ void tma2d_store(const CUtensorMap* m, int c0, int c1, uint32_t src) {
  asm volatile("cp.async.bulk.tensor.2d.global.shared::cta.bulk_group [%0, {%2, %3}], [%1];"
               ::"l"(m), "r"(src), "r"(c0), "r"(c1) : "memory");
}
__device__ __forceinline__ void tma3d_store(const CUtensorMap* m, int c0, int c1, int c2, uint32_t src) {
  asm volatile("cp.async.bulk.tensor.3d.global.shared::cta.bulk_group [%0, {%2, %3, %4}], [%1];"
               ::"l"(m), "r"(src), "r"(c0), "r"(c1), "r"(c2) : "memory");
}
__device__ __forceinline__ void bulk_g2s(uint32_t dst, const void* src, uint32_t bytes, uint32_t bar) {
  asm volatile("cp.async.bulk.shared::cluster.global.mbarrier::complete_tx::bytes [%0], [%1], %2, [%3];"
               ::"r"(dst), "l"(src), "r"(bytes), "r"(bar) : "memory");
}
__device__ __forceinline__ void red_relaxed_add(unsigned* p, unsigned v) {
  asm volatile("red.relaxed.gpu.global.add.u32 [%0], %1;" ::"l"(p), "r"(v) : "memory");
}
__device__ __forceinline__ void bulk_commit() { asm volatile("cp.async.bulk.commit_group;" ::: "memory"); }
__device__ __forceinline__ void bulk_wait_read0() { asm volatile("cp.async.bulk.wait_group.read 0;" ::: "memory"); }
__device__ __forceinline__ void bulk_wait0() { asm volatile("cp.async.bulk.wait_group 0;" ::: "memory"); }
__device__ __forceinline__ void prefetch_tmap(const CUtensorMap* m) { asm volatile("prefetch.tensormap [%0];" ::"l"(m) : "memory"); }

__device__ __forceinline__ void wg_fence() { asm volatile("wgmma.fence.sync.aligned;" ::: "memory"); }
__device__ __forceinline__ void wg_commit() { asm volatile("wgmma.commit_group.sync.aligned;" ::: "memory"); }
template <int N> __device__ __forceinline__ void wg_wait() { asm volatile("wgmma.wait_group.sync.aligned %0;" ::"n"(N) : "memory"); }
__device__ __forceinline__ uint64_t make_desc64(uint32_t addr, uint32_t lbo, uint32_t sbo) {
  return (uint64_t)((addr & 0x3FFFF) >> 4) | ((uint64_t)(lbo >> 4) << 16) | ((uint64_t)(sbo >> 4) << 32) | (2ull << 62);
}
__device__ __forceinline__ uint64_t make_desc(uint32_t addr, uint32_t lbo, uint32_t sbo) {
  return (uint64_t)((addr & 0x3FFFF) >> 4) | ((uint64_t)(lbo >> 4) << 16) | ((uint64_t)(sbo >> 4) << 32) | (1ull << 62);
}
__device__ __forceinline__ void ldsm_x4(uint32_t (&r)[4], uint32_t a) {
  asm volatile("ldmatrix.sync.aligned.m8n8.x4.shared.b16 {%0,%1,%2,%3}, [%4];" : "=r"(r[0]), "=r"(r[1]), "=r"(r[2]), "=r"(r[3]) : "r"(a) : "memory");
}
__device__ __forceinline__ void ldsm_x4(uint32_t& r0, uint32_t& r1, uint32_t& r2, uint32_t& r3, uint32_t a) {
  asm volatile("ldmatrix.sync.aligned.m8n8.x4.shared.b16 {%0,%1,%2,%3}, [%4];" : "=r"(r0), "=r"(r1), "=r"(r2), "=r"(r3) : "r"(a) : "memory");
}
__device__ __forceinline__ void ldsm_x4_t(uint32_t& r0, uint32_t& r1, uint32_t& r2, uint32_t& r3, uint32_t a) {
  asm volatile("ldmatrix.sync.aligned.m8n8.x4.trans.shared.b16 {%0,%1,%2,%3}, [%4];" : "=r"(r0), "=r"(r1), "=r"(r2), "=r"(r3) : "r"(a) : "memory");
}
__device__ __forceinline__ void stsm_x4(uint32_t a, uint32_t r0, uint32_t r1, uint32_t r2, uint32_t r3) {
  asm volatile("stmatrix.sync.aligned.m8n8.x4.shared.b16 [%0], {%1,%2,%3,%4};" ::"r"(a), "r"(r0), "r"(r1), "r"(r2), "r"(r3) : "memory");
}
__device__ __forceinline__ void stsm_x4_t(uint32_t a, uint32_t r0, uint32_t r1, uint32_t r2, uint32_t r3) {
  asm volatile("stmatrix.sync.aligned.m8n8.x4.trans.shared.b16 [%0], {%1,%2,%3,%4};" ::"r"(a), "r"(r0), "r"(r1), "r"(r2), "r"(r3) : "memory");
}
__device__ __forceinline__ void hmma(float (&c)[4], uint32_t a0, uint32_t a1, uint32_t a2, uint32_t a3, uint32_t b0, uint32_t b1) {
  asm volatile("mma.sync.aligned.m16n8k16.row.col.f32.bf16.bf16.f32 {%0,%1,%2,%3}, {%4,%5,%6,%7}, {%8,%9}, {%0,%1,%2,%3};"
               : "+f"(c[0]), "+f"(c[1]), "+f"(c[2]), "+f"(c[3]) : "r"(a0), "r"(a1), "r"(a2), "r"(a3), "r"(b0), "r"(b1));
}
__device__ __forceinline__ uint32_t lds32(uint32_t a) { uint32_t v; asm volatile("ld.shared.u32 %0, [%1];" : "=r"(v) : "r"(a) : "memory"); return v; }
__device__ __forceinline__ uint32_t lds32v(uint32_t a) { uint32_t v; asm volatile("ld.volatile.shared.u32 %0, [%1];" : "=r"(v) : "r"(a) : "memory"); return v; }
__device__ __forceinline__ uint4 lds128(uint32_t a) {
  uint4 v; asm volatile("ld.shared.v4.u32 {%0,%1,%2,%3}, [%4];" : "=r"(v.x), "=r"(v.y), "=r"(v.z), "=r"(v.w) : "r"(a) : "memory"); return v;
}
__device__ __forceinline__ void sts128(uint32_t a, uint4 v) {
  asm volatile("st.shared.v4.u32 [%0], {%1,%2,%3,%4};" ::"r"(a), "r"(v.x), "r"(v.y), "r"(v.z), "r"(v.w) : "memory");
}
__device__ __forceinline__ void sts64(uint32_t a, uint32_t x, uint32_t y) { asm volatile("st.shared.v2.u32 [%0], {%1,%2};" ::"r"(a), "r"(x), "r"(y) : "memory"); }
__device__ __forceinline__ uint32_t bmul2(uint32_t a, uint32_t b) { uint32_t d; asm("mul.rn.bf16x2 %0, %1, %2;" : "=r"(d) : "r"(a), "r"(b)); return d; }
__device__ __forceinline__ uint32_t badd2(uint32_t a, uint32_t b) { uint32_t d; asm("add.rn.bf16x2 %0, %1, %2;" : "=r"(d) : "r"(a), "r"(b)); return d; }
__device__ __forceinline__ uint32_t bsub2(uint32_t a, uint32_t b) { uint32_t d; asm("sub.rn.bf16x2 %0, %1, %2;" : "=r"(d) : "r"(a), "r"(b)); return d; }
__device__ __forceinline__ uint32_t bfma2(uint32_t a, uint32_t b, uint32_t c) { uint32_t d; asm("fma.rn.bf16x2 %0, %1, %2, %3;" : "=r"(d) : "r"(a), "r"(b), "r"(c)); return d; }
__device__ __forceinline__ uint32_t bmax2(uint32_t a, uint32_t b) { uint32_t d; asm("max.bf16x2 %0, %1, %2;" : "=r"(d) : "r"(a), "r"(b)); return d; }
__device__ __forceinline__ uint32_t pack_bf16(float lo, float hi) { uint32_t d; asm("cvt.rn.bf16x2.f32 %0, %1, %2;" : "=r"(d) : "f"(hi), "f"(lo)); return d; }
__device__ __forceinline__ float bf16_round(float x) { return __bfloat162float(__float2bfloat16_rn(x)); }
__device__ __forceinline__ float sqrt_approx(float x) { float y; asm("sqrt.approx.f32 %0, %1;" : "=f"(y) : "f"(x)); return y; }
__device__ __forceinline__ float rcp_approx(float x) { float y; asm("rcp.approx.f32 %0, %1;" : "=f"(y) : "f"(x)); return y; }
__device__ __forceinline__ uint32_t dup_bf16(float x) { return pack_bf16(x, x); }

__device__ __forceinline__ void wgmma_rs_n128(float (&d)[64], const uint32_t (&a)[4], uint64_t db, int sc) {
  asm volatile("{\n.reg .pred p;\nsetp.ne.b32 p, %69, 0;\n"
    "wgmma.mma_async.sync.aligned.m64n128k16.f32.bf16.bf16 "
    "{%0,%1,%2,%3,%4,%5,%6,%7,%8,%9,%10,%11,%12,%13,%14,%15,%16,%17,%18,%19,%20,%21,%22,%23,%24,%25,%26,%27,%28,%29,%30,%31,%32,%33,%34,%35,%36,%37,%38,%39,%40,%41,%42,%43,%44,%45,%46,%47,%48,%49,%50,%51,%52,%53,%54,%55,%56,%57,%58,%59,%60,%61,%62,%63}, "
    "{%64,%65,%66,%67}, %68, p, 1, 1, 1;\n}\n"
    : "+f"(d[0]),"+f"(d[1]),"+f"(d[2]),"+f"(d[3]),"+f"(d[4]),"+f"(d[5]),"+f"(d[6]),"+f"(d[7]),"+f"(d[8]),"+f"(d[9]),"+f"(d[10]),"+f"(d[11]),"+f"(d[12]),"+f"(d[13]),"+f"(d[14]),"+f"(d[15]),"+f"(d[16]),"+f"(d[17]),"+f"(d[18]),"+f"(d[19]),"+f"(d[20]),"+f"(d[21]),"+f"(d[22]),"+f"(d[23]),"+f"(d[24]),"+f"(d[25]),"+f"(d[26]),"+f"(d[27]),"+f"(d[28]),"+f"(d[29]),"+f"(d[30]),"+f"(d[31]),"+f"(d[32]),"+f"(d[33]),"+f"(d[34]),"+f"(d[35]),"+f"(d[36]),"+f"(d[37]),"+f"(d[38]),"+f"(d[39]),"+f"(d[40]),"+f"(d[41]),"+f"(d[42]),"+f"(d[43]),"+f"(d[44]),"+f"(d[45]),"+f"(d[46]),"+f"(d[47]),"+f"(d[48]),"+f"(d[49]),"+f"(d[50]),"+f"(d[51]),"+f"(d[52]),"+f"(d[53]),"+f"(d[54]),"+f"(d[55]),"+f"(d[56]),"+f"(d[57]),"+f"(d[58]),"+f"(d[59]),"+f"(d[60]),"+f"(d[61]),"+f"(d[62]),"+f"(d[63])
    : "r"(a[0]),"r"(a[1]),"r"(a[2]),"r"(a[3]),"l"(db),"r"(sc));
}
__device__ __forceinline__ void wgmma_ss_n112(float (&d)[56], uint64_t da, uint64_t db, int sc) {
  asm volatile("{\n.reg .pred p;\nsetp.ne.b32 p, %58, 0;\n"
    "wgmma.mma_async.sync.aligned.m64n112k16.f32.bf16.bf16 "
    "{%0,%1,%2,%3,%4,%5,%6,%7,%8,%9,%10,%11,%12,%13,%14,%15,%16,%17,%18,%19,%20,%21,%22,%23,%24,%25,%26,%27,%28,%29,%30,%31,%32,%33,%34,%35,%36,%37,%38,%39,%40,%41,%42,%43,%44,%45,%46,%47,%48,%49,%50,%51,%52,%53,%54,%55}, "
    "%56, %57, p, 1, 1, 0, 1;\n}\n"
    : "+f"(d[0]),"+f"(d[1]),"+f"(d[2]),"+f"(d[3]),"+f"(d[4]),"+f"(d[5]),"+f"(d[6]),"+f"(d[7]),"+f"(d[8]),"+f"(d[9]),"+f"(d[10]),"+f"(d[11]),"+f"(d[12]),"+f"(d[13]),"+f"(d[14]),"+f"(d[15]),"+f"(d[16]),"+f"(d[17]),"+f"(d[18]),"+f"(d[19]),"+f"(d[20]),"+f"(d[21]),"+f"(d[22]),"+f"(d[23]),"+f"(d[24]),"+f"(d[25]),"+f"(d[26]),"+f"(d[27]),"+f"(d[28]),"+f"(d[29]),"+f"(d[30]),"+f"(d[31]),"+f"(d[32]),"+f"(d[33]),"+f"(d[34]),"+f"(d[35]),"+f"(d[36]),"+f"(d[37]),"+f"(d[38]),"+f"(d[39]),"+f"(d[40]),"+f"(d[41]),"+f"(d[42]),"+f"(d[43]),"+f"(d[44]),"+f"(d[45]),"+f"(d[46]),"+f"(d[47]),"+f"(d[48]),"+f"(d[49]),"+f"(d[50]),"+f"(d[51]),"+f"(d[52]),"+f"(d[53]),"+f"(d[54]),"+f"(d[55])
    : "l"(da),"l"(db),"r"(sc));
}
__device__ __forceinline__ void wgmma_rs_n64(float (&d)[32], const uint32_t (&a)[4], uint64_t db, int sc) {
  asm volatile("{\n.reg .pred p;\nsetp.ne.b32 p, %37, 0;\n"
    "wgmma.mma_async.sync.aligned.m64n64k16.f32.bf16.bf16 "
    "{%0,%1,%2,%3,%4,%5,%6,%7,%8,%9,%10,%11,%12,%13,%14,%15,%16,%17,%18,%19,%20,%21,%22,%23,%24,%25,%26,%27,%28,%29,%30,%31}, "
    "{%32,%33,%34,%35}, %36, p, 1, 1, 1;\n}\n"
    : "+f"(d[0]),"+f"(d[1]),"+f"(d[2]),"+f"(d[3]),"+f"(d[4]),"+f"(d[5]),"+f"(d[6]),"+f"(d[7]),"+f"(d[8]),"+f"(d[9]),"+f"(d[10]),"+f"(d[11]),"+f"(d[12]),"+f"(d[13]),"+f"(d[14]),"+f"(d[15]),"+f"(d[16]),"+f"(d[17]),"+f"(d[18]),"+f"(d[19]),"+f"(d[20]),"+f"(d[21]),"+f"(d[22]),"+f"(d[23]),"+f"(d[24]),"+f"(d[25]),"+f"(d[26]),"+f"(d[27]),"+f"(d[28]),"+f"(d[29]),"+f"(d[30]),"+f"(d[31])
    : "r"(a[0]),"r"(a[1]),"r"(a[2]),"r"(a[3]),"l"(db),"r"(sc));
}

constexpr int SCHED_R0 = 1, SCHED_S0 = 4, SCHED_R1 = 1, SCHED_S1 = 5;
constexpr int G2_LAST = 14 - SCHED_S0 - SCHED_S1;
static_assert(G2_LAST <= NSLOT, "the last chunk is issued without releasing slots");
constexpr int LAG_STAGE = 2;

__device__ __forceinline__ int wcol(int p, int f) { return ((f & 1) ? 32 : 0) + 64 * p; }

struct Ring {
  uint32_t slot, phase;
  __device__ __forceinline__ void next() { if (++slot == NSLOT) { slot = 0; phase ^= 1; } }
};

__device__ __forceinline__ void release_slot(uint32_t sb, uint32_t slot, bool leader) {
  if (leader) mbar_arrive(sb + OFF_BAR + 8 * (B_EMPTY + slot));
}

template <bool FIRST>
__device__ __forceinline__ void gemm1_pass(float (&acc)[64], uint32_t (&xa)[28][4],
                                           const uint32_t (&m2)[2], const uint32_t (&rh2)[2], const uint32_t (&rl2)[2],
                                           Ring& rg, uint32_t sb, bool leader, int cw, int lane) {
  uint32_t prev = 0;
#pragma unroll
  for (int s = 0; s < 4; ++s) {
    if (FIRST) {
#pragma unroll
      for (int kk = 7 * s; kk < 7 * s + 7; ++kk) {
#pragma unroll
        for (int i = 0; i < 4; ++i) {
          const uint32_t d = bsub2(xa[kk][i], m2[i & 1]);
          xa[kk][i] = bfma2(d, rh2[i & 1], bmul2(d, rl2[i & 1]));
        }
      }
      if (s == 0 && cw == 1) bar_sync(3, 256);
    }
    mbar_wait(sb + OFF_BAR + 8 * (B_FULL + rg.slot), rg.phase);
    const uint64_t db = make_desc(sb + OFF_RING + rg.slot * SLOT_BYTES, 14336, 1024);
    wg_fence();
#pragma unroll
    for (int kk = 0; kk < 7; ++kk) wgmma_rs_n128(acc, xa[7 * s + kk], db + kk * 128, (s == 0 && kk == 0) ? 0 : 1);
    wg_commit();
    if (FIRST && cw == 0 && s == LAG_STAGE) asm volatile("bar.arrive 3, 256;" ::: "memory");
    if (!FIRST && s == 0) {
      fence_async_smem();
      __syncwarp();
      if (lane == 0) mbar_arrive(sb + OFF_BAR + 8 * (B_HSTF + cw));
    }
    if (s > 0) { wg_wait<1>(); release_slot(sb, prev, leader); }
    prev = rg.slot;
    rg.next();
  }
  wg_wait<0>();
  release_slot(sb, prev, leader);
}

__device__ __forceinline__ void gemm1_pass_half(float (&acc)[32], const uint32_t (&xa)[28][4], Ring& rg, uint32_t sb, bool leader, int cw, int lane) {
  uint32_t prev = 0;
#pragma unroll
  for (int s = 0; s < 2; ++s) {
    mbar_wait(sb + OFF_BAR + 8 * (B_FULL + rg.slot), rg.phase);
    const uint64_t db = make_desc64(sb + OFF_RING + rg.slot * SLOT_BYTES, 14336, 512);
    wg_fence();
#pragma unroll
    for (int kk = 0; kk < 14; ++kk) wgmma_rs_n64(acc, xa[14 * s + kk], db + kk * 64, (s == 0 && kk == 0) ? 0 : 1);
    wg_commit();
    if (s == 0) {
      fence_async_smem();
      __syncwarp();
      if (lane == 0) mbar_arrive(sb + OFF_BAR + 8 * (B_HSTF + cw));
    } else {
      wg_wait<1>();
      release_slot(sb, prev, leader);
    }
    prev = rg.slot;
    rg.next();
  }
  wg_wait<0>();
  release_slot(sb, prev, leader);
}

__device__ __forceinline__ void gemm2_chunk(float (&acc2)[56], int& st, int send, Ring& rg, uint32_t sb, bool leader, int cw) {
  const int st0 = st;
  uint32_t prev = 0;
#pragma unroll 1
  for (; st < send; ++st) {
    mbar_wait(sb + OFF_BAR + 8 * (B_FULL + rg.slot), rg.phase);
    const uint32_t base = sb + OFF_RING + rg.slot * SLOT_BYTES;
    const uint64_t da = make_desc(base + cw * 8192, 16, 1024);
    const uint64_t db = make_desc(base + 16384, 8192, 1024);
    wg_fence();
#pragma unroll
    for (int kk = 0; kk < 4; ++kk) wgmma_ss_n112(acc2, da + kk * 2, db + kk * 128, (st == 0 && kk == 0) ? 0 : 1);
    wg_commit();
    if (st > st0) { wg_wait<1>(); release_slot(sb, prev, leader); }
    prev = rg.slot;
    rg.next();
  }
  wg_wait<0>();
  if (st > st0) release_slot(sb, prev, leader);
}

template <int NG>
__device__ __forceinline__ void gemm1_stage_h(const float* gate, const float* up, uint32_t saddr, uint32_t srow, int lane, uint32_t choff) {
#pragma unroll
  for (int j = 0; j < NG; j += 2) {
    uint32_t h[4];
#pragma unroll
    for (int i = 0; i < 4; ++i) {
      const int o = 4 * (j + (i >> 1)) + 2 * (i & 1);
      h[i] = bmul2(bmax2(pack_bf16(gate[o], gate[o + 1]), 0u), pack_bf16(up[o], up[o + 1]));
    }
    stsm_x4(saddr + (((choff + j + (lane >> 4)) ^ (srow & 7)) << 4), h[0], h[1], h[2], h[3]);
  }
}

__device__ __forceinline__ void kv_prepass(uint32_t ka, uint32_t va, uint32_t stg, const uint4 w0, int b, int cp) {
  const uint32_t t0 = __byte_perm(w0.x, w0.z, 0x5410), t1 = __byte_perm(w0.x, w0.z, 0x7632);
  const uint32_t t2 = __byte_perm(w0.y, w0.w, 0x5410), t3 = __byte_perm(w0.y, w0.w, 0x7632);
  uint32_t kr[19], vr[16];
#pragma unroll
  for (int i = 0; i < 19; ++i) kr[i] = lds32(ka + cp * 4 + i * 896);
#pragma unroll
  for (int i = 0; i < 16; ++i) vr[i] = lds32(va + cp * 4 + (i >> 2) * SLOT_BYTES + (i & 3) * 896);
  uint32_t o0[8], o1[8];
#pragma unroll
  for (int i = 0; i < 16; i += 2) {
    uint32_t kv[2];
#pragma unroll
    for (int e = 0; e < 2; ++e) {
      uint32_t a = bmul2(kr[i + e], t3);
      a = badd2(a, bmul2(kr[i + e + 1], t2));
      a = badd2(a, bmul2(kr[i + e + 2], t1));
      a = badd2(a, bmul2(kr[i + e + 3], t0));
      kv[e] = bmul2(a, vr[i + e]);
    }
    o0[7 - (i >> 1)] = __byte_perm(kv[1], kv[0], 0x5410);
    o1[7 - (i >> 1)] = __byte_perm(kv[1], kv[0], 0x7632);
  }
  const int c = (2 * cp) / 112;
  const uint32_t dst = stg + c * HC_BYTES + (2 * cp - 112 * c) * 32;
  const uint32_t sw = ((b >> 2) & 1) * 16;
  sts128(dst + sw,             make_uint4(o0[0], o0[1], o0[2], o0[3]));
  sts128(dst + (sw ^ 16),      make_uint4(o0[4], o0[5], o0[6], o0[7]));
  sts128(dst + 32 + sw,        make_uint4(o1[0], o1[1], o1[2], o1[3]));
  sts128(dst + 32 + (sw ^ 16), make_uint4(o1[4], o1[5], o1[6], o1[7]));
}

__global__ void __cluster_dims__(2, 1, 1) __launch_bounds__(NTHREADS, 1)
fused_h3_mlp_kernel(const __grid_constant__ Params P) {
  extern __shared__ __align__(1024) uint8_t smem[];
  const uint32_t sb = smem_u32(smem);
  const int tid = threadIdx.x, warp = tid >> 5;
  const int b = blockIdx.x;
  const int rank = b & 1;
  const int pr = b >> 1, mt = pr & 15, f = (pr >> 4) + 4 * rank;
  const int jq = f & 3, kap = rank;
  const uint32_t bar = sb + OFF_BAR;
  const bool has_conv = b < CONV_CTAS;

  if (tid == 96) prefetch_tmap(&P.tm_xe);
  if (tid == 0) {
    for (int i = 0; i < 7; ++i) mbar_init(bar + 8 * (B_XFULL + i), 1);
    mbar_init(bar + 8 * B_XFREE, 1);
    mbar_init(bar + 8 * B_XFULL2, 1);
    fence_async_smem();
    asm volatile("fence.mbarrier_init.release.cluster;" ::: "memory");
#pragma unroll
    for (int cb = 0; cb < 7; ++cb) mbar_expect_tx(bar + 8 * (B_XFULL + cb), 16384);
  }
  __syncwarp();
  cluster_arrive_relaxed();
  if (tid == 32) {
    for (int i = 0; i < NSLOT; ++i) { mbar_init(bar + 8 * (B_FULL + i), 1); mbar_init(bar + 8 * (B_EMPTY + i), 2); }
    mbar_init(bar + 8 * B_HRAW, 1);
    mbar_init(bar + 8 * B_KVDONE, 1);
    mbar_init(bar + 8 * B_KVFULL, 1);
    mbar_init(bar + 8 * B_CONVRDY, 65);
    mbar_init(bar + 8 * B_EPIFULL, 1);
    mbar_init(bar + 8 * B_YFULL, 8);
    mbar_init(bar + 8 * B_CONVDONE, 8);
    mbar_init(bar + 8 * B_STAT, 8);
    mbar_init(bar + 8 * B_HSTF, 4); mbar_init(bar + 8 * (B_HSTF + 1), 4);
    mbar_init(bar + 8 * B_HSTE, 1); mbar_init(bar + 8 * (B_HSTE + 1), 1);
    fence_async_smem();
  } else if (tid == 64) {
    prefetch_tmap(&P.tm_wg); prefetch_tmap(&P.tm_wu);
  }
  __syncwarp();
  cluster_wait();
  if (tid == 0) {
#pragma unroll
    for (int cb = 0; cb < 2; ++cb)
      tma2d_mc(sb + OFF_RING + 3 * SLOT_BYTES + cb * 16384 + rank * 8192, &P.tm_xe, cb * 64, mt * 128 + rank * 64, bar + 8 * (B_XFULL + cb));
  }
  __syncthreads();
  if (tid == 0) {
#pragma unroll
    for (int cb = 2; cb < 7; ++cb)
      tma2d_mc(sb + OFF_RING + 3 * SLOT_BYTES + cb * 16384 + rank * 8192, &P.tm_xe, cb * 64, mt * 128 + rank * 64, bar + 8 * (B_XFULL + cb));
  }

  if (warp < 4) {
    asm volatile("setmaxnreg.dec.sync.aligned.u32 72;");
    const int tid = fresh_tid(), warp = tid >> 5, lane = tid & 31;
    if (warp == 0) {
      unsigned epoch = 0;
      uint32_t slot = 0, use = 0;
#pragma unroll 1
      for (int n = 0; n < 28; ++n) {
        if (slot >= 3) mbar_wait(bar + 8 * (B_EMPTY + slot), use & 1);
        else if (use > 0) mbar_wait(bar + 8 * (B_EMPTY + slot), (use - 1) & 1);
        const uint32_t fb = bar + 8 * (B_FULL + slot);
        const uint32_t dst = sb + OFF_RING + slot * SLOT_BYTES;
        if (n < 14) {
          if (elect_one()) {
            mbar_expect_tx(fb, 28672);
            if (n < 12) {
              tma3d(dst, &P.tm_wg, wcol(n >> 2, f), f, (n & 3) * 112, fb);
              tma3d(dst + 14336, &P.tm_wu, wcol(n >> 2, f), f, (n & 3) * 112, fb);
            } else {
              tma3d(dst, &P.tm_wgh, (f & 1) ? 0 : 192, f, (n - 12) * 224, fb);
              tma3d(dst + 14336, &P.tm_wuh, (f & 1) ? 0 : 192, f, (n - 12) * 224, fb);
            }
            if (n == 3) {
              const uint32_t kb = bar + 8 * B_KVFULL;
              const int r0 = b * 16;
              if (b == 0) {
                mbar_expect_tx(kb, 16 * 896 * 2);
                bulk_g2s(sb + OFF_KST + 3 * 896, P.k, 16 * 896, kb);
              } else {
                mbar_expect_tx(kb, 19 * 896 + 16 * 896);
                bulk_g2s(sb + OFF_KST, P.k + (size_t)(r0 - 3) * D_DIM, 19 * 896, kb);
              }
#pragma unroll
              for (int c = 0; c < 4; ++c)
                bulk_g2s(sb + OFF_RING + c * SLOT_BYTES + OFF_VTAIL, P.v + (size_t)(r0 + 4 * c) * D_DIM, 4 * 896, kb);
              if (has_conv) {
                const uint32_t hb = bar + 8 * B_HRAW;
                mbar_expect_tx(hb, 4 * 4096);
#pragma unroll
                for (int c = 0; c < 4; ++c)
                  bulk_g2s(sb + OFF_HC + c * HC_BYTES + HC_COPY0 + 32, P.ssm_k + (size_t)(4 * b + c) * S_LEN, 4096, hb);
              }
            }
          }
        } else {
          const int t = n - 14;
          if (t == 0) mbar_wait_parked(bar + 8 * B_KVDONE, 0);
          const int kt = (int)((0xA3D962C851B740ull >> (4 * t)) & 15);
          const int k0 = kap * 896 + kt * 64;
          if (elect_one()) {
            mbar_expect_tx(fb, 32768);
            tma3d(dst + 16384, &P.tm_wd, 0, jq, k0, fb);
            tma3d(dst + 24576, &P.tm_wd, 64, jq, k0, fb);
          }
          if (t == 0) epoch = lds32(sb + OFF_EPOCH);
          if (t == 0 || t == 8) {
            wait_count(&g_sync.cnt_h[(mt * 2 + kap) * 32 + (t ? 16 : 0)], 4u * (late(epoch) + 1));
            fence_async_global();
          }
          __syncwarp();
          if (elect_one()) tma2d(dst, &P.tm_hl, k0, mt * 128, fb);
        }
        __syncwarp();
        if (++slot == NSLOT) { slot = 0; ++use; }
      }
    } else {
      if (warp == 1) {
        if (lane == 0) mbar_expect_tx(bar + 8 * B_XFULL2, 7 * 2048);
        mbar_wait_parked(bar + 8 * (B_XFULL + 2), 0);
        if (lane == 0) {
          prefetch_tmap(&P.tm_hs); prefetch_tmap(&P.tm_kv); prefetch_tmap(&P.tm_wgh); prefetch_tmap(&P.tm_wuh); prefetch_tmap(&P.tm_hh);
          prefetch_tmap(&P.tm_wd); prefetch_tmap(&P.tm_hl); prefetch_tmap(&P.tm_y); prefetch_tmap(&P.tm_yl);
          prefetch_tmap(&P.tm_out);
        }
#pragma unroll 1
        for (int p = 0; p < 4; ++p) {
#pragma unroll 1
          for (int w = 0; w < 2; ++w) {
            mbar_wait_parked(bar + 8 * (B_HSTF + w), p & 1);
            if (lane == 0) {
              if (p < 3) tma3d_store(&P.tm_hs, wcol(p, f), f, mt * 128 + w * 64, sb + OFF_HST + w * 8192);
              else       tma3d_store(&P.tm_hh, 0, 7 * f + ((f & 1) ? 0 : 6), mt * 128 + w * 64, sb + OFF_HST + w * 8192);
              bulk_commit();
              if (p < 3) {
                bulk_wait_read0();
                mbar_arrive(bar + 8 * (B_HSTE + w));
                if (p == 1 && w == 1) {
                  bulk_wait0();
                  red_relaxed_add(&g_sync.cnt_h[(mt * 2 + (f >> 2)) * 32], 1);
                }
              }
            }
            __syncwarp();
          }
        }
        const uint32_t eb = bar + 8 * B_EPIFULL;
        if (lane == 0) {
          bulk_wait0();
          red_relaxed_add(&g_sync.cnt_h[(mt * 2 + (f >> 2)) * 32 + 16], 1);
          mbar_expect_tx(eb, 16384 + 14336);
          tma2d(sb + OFF_HST, &P.tm_xe, jq * 112, mt * 128 + kap * 64, eb);
          tma2d(sb + OFF_HST + 8192, &P.tm_xe, jq * 112 + 64, mt * 128 + kap * 64, eb);
        }
        __syncwarp();
        if (has_conv) {
          mbar_wait_parked(bar + 8 * B_YFULL, 0);
          if (lane == 0) {
#pragma unroll
            for (int i = 0; i < 8; ++i)
              tma3d_store(&P.tm_y, 0, 4 * b + (i >> 1), 16 * (i & 1), sb + OFF_HC + (i >> 1) * HC_BYTES + (i & 1) * 4096);
            bulk_commit();
            bulk_wait0();
            red_relaxed_add(&g_sync.cnt_y[(b / 28) * 32], 1);
          }
          __syncwarp();
        }
        mbar_wait_parked(bar + 8 * B_KVDONE, 0);
        if (lane == 0) mbar_arrive_cta(bar + 8 * B_XFREE, rank ^ 1);
        mbar_wait_parked(bar + 8 * B_CONVDONE, 0);
        wait_count(&g_sync.cnt_y[jq * 32], 28u * (lds32(sb + OFF_EPOCH) + 1));
        fence_async_global();
        __syncwarp();
        if (lane == 0) { tma2d(sb + OFF_C, &P.tm_yl, 0, (mt * 2 + kap) * D_DIM + jq * 112, eb); prefetch_tmap(&P.tm_out); }
      } else {
        const int at = tid - 64;
        const unsigned epoch = ld_relaxed(&g_sync.epoch);
        uint4 wsh[4];
#pragma unroll
        for (int i = 0; i < 4; ++i) {
          const int cp = at + 64 * i;
          wsh[i] = cp < 224 ? __ldg(reinterpret_cast<const uint4*>(P.shift_k) + cp) : make_uint4(0, 0, 0, 0);
        }
        mbar_wait_parked(bar + 8 * B_KVFULL, 0);
        if (b == 0) {
          for (int i = at; i < 3 * 896 / 16; i += 64) sts128(sb + OFF_KST + i * 16, make_uint4(0, 0, 0, 0));
          bar_sync(4, 64);
        }
#pragma unroll
        for (int i = 0; i < 4; ++i) {
          const int cp = at + 64 * i;
          if (cp < 224) kv_prepass(sb + OFF_KST, sb + OFF_RING + OFF_VTAIL, sb + OFF_HC, wsh[i], b, cp);
        }
        fence_async_smem();
        bar_sync(4, 64);
        if (at == 0) {
#pragma unroll
          for (int c = 0; c < 4; ++c) tma2d_store(&P.tm_kv, 16 * b, 112 * c, sb + OFF_HC + c * HC_BYTES);
          bulk_commit();
          asm volatile("st.shared.u32 [%0], %1;" ::"r"(sb + OFF_EPOCH), "r"(epoch) : "memory");
          bulk_wait_read0();
          mbar_arrive(bar + 8 * B_KVDONE);
        }
        bar_sync(4, 64);
        if (at == 0) { bulk_wait0(); red_relaxed_add(&g_sync.cnt_kv, 1); }
        __syncwarp();
        if (has_conv) {
          mbar_wait_parked(bar + 8 * B_HRAW, 0);
#pragma unroll 1
          for (int c = (warp == 2 ? 2 : 0); c < (warp == 2 ? 4 : 2); ++c) {
            const uint32_t hb = sb + OFF_HC + c * HC_BYTES;
            uint4 v[8];
#pragma unroll
            for (int i = 0; i < 8; ++i) v[i] = lds128(hb + HC_COPY0 + 32 + (i * 32 + lane) * 16);
#pragma unroll
            for (int i = 0; i < 8; ++i) {
              uint32_t nx = __shfl_down_sync(0xffffffffu, v[i].x, 1);
              const uint32_t first_next = __shfl_sync(0xffffffffu, v[i < 7 ? i + 1 : 7].x, 0);
              if (lane == 31) nx = i < 7 ? first_next : 0u;
              sts128(hb + 32 + (i * 32 + lane) * 16, make_uint4(__byte_perm(v[i].x, v[i].y, 0x5432), __byte_perm(v[i].y, v[i].z, 0x5432),
                                                                 __byte_perm(v[i].z, v[i].w, 0x5432), __byte_perm(v[i].w, nx, 0x5432)));
            }
            if (lane == 0) {
              sts128(hb + HC_COPY0, make_uint4(0, 0, 0, 0));
              sts128(hb + HC_COPY0 + 16, make_uint4(0, 0, 0, 0));
              sts128(hb, make_uint4(0, 0, 0, 0));
              sts128(hb + 16, make_uint4(0, 0, 0, v[0].x << 16));
            }
          }
          sts128(sb + OFF_U + (at >> 4) * U_BYTES + (at & 15) * 16, make_uint4(0, 0, 0, 0));
          if (warp == 2) {
            wait_count(&g_sync.cnt_kv, (unsigned)NCTA * (late(epoch) + 1));
            if (b == 0 && lane == 0) *(volatile unsigned*)&g_sync.epoch = epoch + 1;
            fence_async_global();
            __syncwarp();
            if (lane == 0) {
              const uint32_t cb = bar + 8 * B_CONVRDY;
              mbar_expect_tx(cb, 4 * 4096);
#pragma unroll
              for (int c = 0; c < 4; ++c) bulk_g2s(sb + OFF_U + c * U_BYTES + 256, g_kvT + (size_t)(4 * b + c) * S_LEN, 4096, cb);
            }
          }
          mbar_arrive(bar + 8 * B_CONVRDY);
        }
      }
    }
    cluster_arrive_relaxed();
    cluster_wait();
  } else {
    asm volatile("setmaxnreg.inc.sync.aligned.u32 216;");
    const int tid = fresh_tid(), warp = tid >> 5, lane = tid & 31;
    const int cw = (warp >> 2) - 1, wq = warp & 3;
    const int g = lane >> 2, t = lane & 3;
    const bool leader = (tid & 127) == 0;
    uint32_t dv = 0;
    if (has_conv) dv = __bfloat16_as_ushort(__ldg(P.ssm_D + 4 * b + ((warp - 4) >> 1)));

    uint32_t xa[28][4];
    uint32_t m2[2], rh2[2], rl2[2];
    {
      float cs[2][4] = {}, q0[2][4] = {}, q1[2][4] = {};
      const uint32_t lrow = cw * 64 + wq * 16 + (lane & 7) + ((lane >> 3) & 1) * 8;
      const uint32_t lch = lane >> 4;
#pragma unroll
      for (int cb = 0; cb < 7; ++cb) {
        mbar_wait(bar + 8 * (B_XFULL + cb), 0);
        const uint32_t boxo = cb < 4 ? OFF_RING + 3 * SLOT_BYTES + cb * 16384 : (cb == 4 ? OFF_HST : OFF_C + (cb - 5) * 16384);
        const uint32_t base = sb + boxo + lrow * 128;
#pragma unroll
        for (int c = 0; c < 4; ++c) {
          const int kk = 4 * cb + c;
          ldsm_x4(xa[kk], base + (((2 * c + lch) ^ (lrow & 7)) << 4));
          hmma(cs[kk & 1], xa[kk][0], xa[kk][1], xa[kk][2], xa[kk][3], 0x3F803F80u, 0x3F803F80u);
          hmma(q0[kk & 1], xa[kk][0], xa[kk][1], xa[kk][2], xa[kk][3], xa[kk][0], xa[kk][2]);
          hmma(q1[kk & 1], xa[kk][0], xa[kk][1], xa[kk][2], xa[kk][3], xa[kk][1], xa[kk][3]);
        }
      }
      bar_sync(1 + cw, 128);
      release_slot(sb, 3, leader);
      release_slot(sb, 4, leader);
      const int src = (lane & ~3) | (g >> 1);
      const float sqa = __shfl_sync(0xffffffffu, (g & 1) ? q0[0][1] + q0[1][1] : q0[0][0] + q0[1][0], src);
      const float sqb = __shfl_sync(0xffffffffu, (g & 1) ? q1[0][3] + q1[1][3] : q1[0][2] + q1[1][2], src);
#pragma unroll
      for (int r = 0; r < 2; ++r) {
        const float sum = cs[0][2 * r] + cs[1][2 * r];
        const float sq = r ? sqb : sqa;
        const float mean = sum * (1.0f / D_DIM);
        const float var = fmaxf(sq * (1.0f / D_DIM) - mean * mean, 0.0f);
        const float den = bf16_round(sqrt_approx(bf16_round(bf16_round(var) + 1e-5f)));
        const float rinv = rcp_approx(den);
        const float rh = bf16_round(rinv);
        m2[r] = dup_bf16(mean); rh2[r] = dup_bf16(rh); rl2[r] = dup_bf16(rinv - rh);
      }
    }

    Ring rg{0, 0};
    {
      const uint32_t srow = wq * 16 + (lane & 7) + ((lane >> 3) & 1) * 8;
      const uint32_t saddr = sb + OFF_HST + cw * 8192 + srow * 128;
      {
        float acc[64];
        gemm1_pass<true>(acc, xa, m2, rh2, rl2, rg, sb, leader, cw, lane);
        gemm1_stage_h<8>(acc, acc + 32, saddr, srow, lane, 0);
        if (t == 0 && cw == kap) {
#pragma unroll
          for (int r = 0; r < 2; ++r)
            sts64(sb + OFF_STAT + (wq * 16 + g + 8 * r) * 8, (m2[r] & 0xffffu) | (rh2[r] << 16), rl2[r] & 0xffffu);
        }
        __syncwarp();
        if (lane == 0) mbar_arrive(bar + 8 * B_STAT);
#pragma unroll 1
        for (int p = 1; p < 3; ++p) {
          gemm1_pass<false>(acc, xa, m2, rh2, rl2, rg, sb, leader, cw, lane);
          mbar_wait(bar + 8 * (B_HSTE + cw), (p - 1) & 1);
          gemm1_stage_h<8>(acc, acc + 32, saddr, srow, lane, 0);
        }
      }
      float acch[32];
      gemm1_pass_half(acch, xa, rg, sb, leader, cw, lane);
      mbar_wait(bar + 8 * (B_HSTE + cw), 0);
      gemm1_stage_h<4>(acch, acch + 16, saddr, srow, lane, 0);
      fence_async_smem();
      __syncwarp();
      if (lane == 0) mbar_arrive(bar + 8 * (B_HSTF + cw));
    }

    const int cwarp = warp - 4, cc_ = cwarp >> 1, hh = cwarp & 1;
    const uint32_t ub = sb + OFF_U + cc_ * U_BYTES;
    const uint32_t hb = sb + OFF_HC + cc_ * HC_BYTES;
    float cacc[16][4];
#pragma unroll
    for (int i = 0; i < 16; ++i) { cacc[i][0] = cacc[i][1] = cacc[i][2] = cacc[i][3] = 0.f; }
    const uint32_t abase = hb + ((g & 1) ? HC_COPY0 + 4 * (((1 + g) >> 1) + t) : 4 * ((g >> 1) + t));
    float acc2[56];
    uint32_t dfrag = 0;
    if (has_conv) {
      const int e = 7 - g - 2 * t;
      dv = late(dv);
      dfrag = (e == 0) ? dv : (e == 1 ? dv << 16 : 0u);
      mbar_wait(bar + 8 * B_CONVRDY, 0);
    }
    int r = 4 * hh, st = 0;
#pragma unroll 1
    for (int seg = 0; seg < 3; ++seg) {
      if (has_conv) {
        const int rend = seg == 2 ? 4 * hh + 4 : r + (seg == 0 ? SCHED_R0 : SCHED_R1);
#pragma unroll 1
        for (; r < rend; ++r) {
          const uint32_t R = 8 + 8 * (lane >> 4) + (lane & 7) - r;
          const uint32_t baddr = ub + 32 * R + 16 * (((lane >> 3) & 1) ^ ((R >> 2) & 1));
          const uint32_t aaddr = abase + 32 * r;
          uint32_t bf[16][2];
#pragma unroll
          for (int jp = 7; jp >= 0; --jp) ldsm_x4(bf[2 * jp][0], bf[2 * jp][1], bf[2 * jp + 1][0], bf[2 * jp + 1][1], baddr + 512 * jp);
          if (r == 0) {
#pragma unroll
            for (int tau = 15; tau >= 0; --tau) hmma(cacc[tau], 0u, dfrag, dfrag, 0u, bf[tau][0], bf[tau][1]);
          }
          uint32_t aL[4], aS[4];
          aL[0] = lds32v(aaddr); aL[1] = lds32v(aaddr + 16); aL[3] = lds32v(aaddr + 32);
          aS[0] = lds32v(aaddr + 256 * 15); aS[1] = lds32v(aaddr + 256 * 15 + 16); aS[3] = lds32v(aaddr + 256 * 15 + 32);
          aL[2] = lds32v(aaddr + 16); aS[2] = lds32v(aaddr + 256 * 15 + 16);
#pragma unroll
          for (int q = 0; q < 8; ++q) {
            const int q2 = 15 - q;
            uint32_t nL[4] = {0, 0, 0, 0}, nS[4] = {0, 0, 0, 0};
            if (q < 7) {
              nL[0] = lds32v(aaddr + 256 * (q + 1)); nL[1] = lds32v(aaddr + 256 * (q + 1) + 16); nL[3] = lds32v(aaddr + 256 * (q + 1) + 32);
              nS[0] = lds32v(aaddr + 256 * (q2 - 1)); nS[1] = lds32v(aaddr + 256 * (q2 - 1) + 16); nS[3] = lds32v(aaddr + 256 * (q2 - 1) + 32);
              nL[2] = lds32v(aaddr + 256 * (q + 1) + 16); nS[2] = lds32v(aaddr + 256 * (q2 - 1) + 16);
            }
#pragma unroll
            for (int tau = 15; tau >= 8; --tau) hmma(cacc[tau], aL[0], aL[1], aL[2], aL[3], bf[tau - q][0], bf[tau - q][1]);
#pragma unroll
            for (int tau = 15; tau >= q2; --tau) hmma(cacc[tau], aS[0], aS[1], aS[2], aS[3], bf[tau - q2][0], bf[tau - q2][1]);
#pragma unroll
            for (int tau = 7; tau >= q; --tau) hmma(cacc[tau], aL[0], aL[1], aL[2], aL[3], bf[tau - q][0], bf[tau - q][1]);
#pragma unroll
            for (int i = 0; i < 4; ++i) { aL[i] = nL[i]; aS[i] = nS[i]; }
          }
        }
        if (seg == 2) {
          bar_sync(5 + cc_, 64);
          const uint32_t oth = hb + (1 - hh) * 4096 + lane * 16;
#pragma unroll
          for (int i = 0; i < 8; ++i)
            sts128(oth + i * 512, make_uint4(__float_as_uint(hh ? cacc[i][0] : cacc[8 + i][0]), __float_as_uint(hh ? cacc[i][1] : cacc[8 + i][1]),
                                             __float_as_uint(hh ? cacc[i][2] : cacc[8 + i][2]), __float_as_uint(hh ? cacc[i][3] : cacc[8 + i][3])));
          bar_sync(5 + cc_, 64);
          const uint32_t area = hb + hh * 4096;
          uint32_t yp[8][2];
#pragma unroll
          for (int i = 0; i < 8; ++i) {
            const uint4 v = lds128(area + i * 512 + lane * 16);
            yp[i][0] = pack_bf16((hh ? cacc[8 + i][0] : cacc[i][0]) + __uint_as_float(v.x), (hh ? cacc[8 + i][1] : cacc[i][1]) + __uint_as_float(v.y));
            yp[i][1] = pack_bf16((hh ? cacc[8 + i][2] : cacc[i][2]) + __uint_as_float(v.z), (hh ? cacc[8 + i][3] : cacc[i][3]) + __uint_as_float(v.w));
          }
          __syncwarp();
#pragma unroll
          for (int i = 0; i < 8; i += 2) {
            const uint32_t bl = 8 * (i + (lane >> 4)) + (lane & 7);
            stsm_x4_t(area + 32 * bl + 16 * (((lane >> 3) & 1) ^ ((bl >> 2) & 1)), yp[i][0], yp[i][1], yp[i + 1][0], yp[i + 1][1]);
          }
          fence_async_smem();
          __syncwarp();
          if (lane == 0) mbar_arrive(bar + 8 * B_YFULL);
        }
      }
      if (seg < 2) {
        bar_sync(3, 256);
        gemm2_chunk(acc2, st, st + (seg == 0 ? SCHED_S0 : SCHED_S1), rg, sb, leader, cw);
      }
    }
    __syncwarp();
    if (lane == 0) mbar_arrive(bar + 8 * B_CONVDONE);
    const int t128 = tid & 127;
    if (cw == kap) cluster_arrive_relaxed();
    bar_sync(3, 256);
    {
#pragma unroll
      for (int i = 0; i < G2_LAST; ++i) {
        mbar_wait(bar + 8 * (B_FULL + rg.slot), rg.phase);
        const uint32_t base = sb + OFF_RING + rg.slot * SLOT_BYTES;
        const uint64_t da = make_desc(base + cw * 8192, 16, 1024);
        const uint64_t db = make_desc(base + 16384, 8192, 1024);
        wg_fence();
#pragma unroll
        for (int kk = 0; kk < 4; ++kk) wgmma_ss_n112(acc2, da + kk * 2, db + kk * 128, 1);
        wg_commit();
        rg.next();
      }
      wg_wait<0>();
    }

    if (cw != kap) {
      mbar_wait(bar + 8 * B_XFREE, 0);
      const uint32_t dst = mapa(sb + OFF_HC + t128 * 16, rank ^ 1), rb = mapa(bar + 8 * B_XFULL2, rank ^ 1);
#pragma unroll
      for (int q = 0; q < 7; ++q)
        st_async_v4(dst + q * 2048, pack_bf16(acc2[8 * q], acc2[8 * q + 1]), pack_bf16(acc2[8 * q + 2], acc2[8 * q + 3]),
                    pack_bf16(acc2[8 * q + 4], acc2[8 * q + 5]), pack_bf16(acc2[8 * q + 6], acc2[8 * q + 7]), rb);
      cluster_arrive_relaxed();
    } else {
      if (lane == 0) prefetch_tmap(&P.tm_out);
      mbar_wait(bar + 8 * B_EPIFULL, 0);
      uint32_t o1[14][2];
      {
        uint32_t em2[2], erh2[2], erl2[2];
        mbar_wait(bar + 8 * B_STAT, 0);
#pragma unroll
        for (int rr = 0; rr < 2; ++rr) {
          uint32_t s0, s1;
          asm volatile("ld.shared.v2.u32 {%0,%1}, [%2];" : "=r"(s0), "=r"(s1) : "r"(sb + OFF_STAT + (wq * 16 + g + 8 * rr) * 8) : "memory");
          em2[rr] = __byte_perm(s0, 0, 0x1010); erh2[rr] = __byte_perm(s0, 0, 0x3232); erl2[rr] = __byte_perm(s1, 0, 0x1010);
        }
        const uint32_t xrow = wq * 16 + (lane & 7) + ((lane >> 3) & 1) * 8;
        uint32_t x[7][4], yf[7][4];
#pragma unroll
        for (int jp = 0; jp < 7; ++jp) {
          const int jn = 2 * jp;
          const uint32_t chunk = (jn & 7) + (lane >> 4);
          ldsm_x4(x[jp][0], x[jp][1], x[jp][2], x[jp][3], sb + OFF_HST + (jn >> 3) * 8192 + xrow * 128 + ((chunk ^ (xrow & 7)) << 4));
          const uint32_t chrow = 8 * (jn + (lane >> 4)) + (lane & 7);
          const uint32_t tc = (2 * wq + ((lane >> 3) & 1)) ^ kap;
          ldsm_x4_t(yf[jp][0], yf[jp][1], yf[jp][2], yf[jp][3], sb + OFF_C + chrow * 128 + ((tc ^ (chrow & 7)) << 4));
        }
#pragma unroll
        for (int jp = 0; jp < 7; ++jp) {
#pragma unroll
          for (int i = 0; i < 4; ++i) {
            const int rr = i & 1;
            const uint32_t d = bsub2(x[jp][i], em2[rr]);
            const uint32_t xn = bfma2(d, erh2[rr], bmul2(d, erl2[rr]));
            o1[2 * jp + (i >> 1)][rr] = badd2(x[jp][i], bmul2(xn, yf[jp][i]));
          }
        }
      }
      mbar_wait(bar + 8 * B_XFULL2, 0);
      uint4 pv[7];
#pragma unroll
      for (int q = 0; q < 7; ++q) pv[q] = lds128(sb + OFF_HC + q * 2048 + t128 * 16);
      const uint32_t xrow2 = wq * 16 + (lane & 7) + ((lane >> 3) & 1) * 8;
#pragma unroll
      for (int jn = 0; jn < 14; jn += 2) {
        const uint32_t pw[4] = {pv[jn >> 1].x, pv[jn >> 1].y, pv[jn >> 1].z, pv[jn >> 1].w};
        uint32_t o[4];
#pragma unroll
        for (int i = 0; i < 4; ++i) {
          const int q = jn + (i >> 1), rr = i & 1;
          o[i] = badd2(o1[q][rr], pack_bf16(acc2[4 * q + 2 * rr] + __uint_as_float(pw[i] << 16),
                                            acc2[4 * q + 2 * rr + 1] + __uint_as_float(pw[i] & 0xffff0000u)));
        }
        const uint32_t chunk = (jn & 7) + (lane >> 4);
        stsm_x4(sb + OFF_HST + (jn >> 3) * 8192 + xrow2 * 128 + ((chunk ^ (xrow2 & 7)) << 4), o[0], o[1], o[2], o[3]);
      }
      fence_async_smem();
      __syncwarp();
      if (lane == 0) {
        tma3d_store(&P.tm_out, 0, jq, mt * 128 + kap * 64 + wq * 16, sb + OFF_HST + wq * 2048);
        tma3d_store(&P.tm_out, 64, jq, mt * 128 + kap * 64 + wq * 16, sb + OFF_HST + 8192 + wq * 2048);
        bulk_commit();
        bulk_wait_read0();
      }
    }
    cluster_wait();
  }
}

typedef CUresult (*EncodeFn)(CUtensorMap*, CUtensorMapDataType, cuuint32_t, void*, const cuuint64_t*, const cuuint64_t*,
                             const cuuint32_t*, const cuuint32_t*, CUtensorMapInterleave, CUtensorMapSwizzle,
                             CUtensorMapL2promotion, CUtensorMapFloatOOBfill);

void encode(EncodeFn fn, CUtensorMap* m, const void* base, int rank, const cuuint64_t* dims, const cuuint64_t* strides, const cuuint32_t* box,
            CUtensorMapSwizzle swz = CU_TENSOR_MAP_SWIZZLE_128B) {
  cuuint32_t es[3] = {1, 1, 1};
  fn(m, CU_TENSOR_MAP_DATA_TYPE_BFLOAT16, (cuuint32_t)rank, const_cast<void*>(base), dims, strides, box, es,
     CU_TENSOR_MAP_INTERLEAVE_NONE, swz, CU_TENSOR_MAP_L2_PROMOTION_L2_128B, CU_TENSOR_MAP_FLOAT_OOB_FILL_NONE);
}
void encode2(EncodeFn fn, CUtensorMap* m, const void* base, uint64_t cols, uint64_t rows, uint32_t bc, uint32_t br) {
  cuuint64_t d[2] = {cols, rows}; cuuint64_t s[1] = {cols * 2}; cuuint32_t bx[2] = {bc, br};
  encode(fn, m, base, 2, d, s, bx);
}
void encode3(EncodeFn fn, CUtensorMap* m, const void* base, uint64_t w, uint64_t nslice, uint64_t rows, uint32_t bc, uint32_t br) {
  cuuint64_t d[3] = {w, nslice, rows}; cuuint64_t s[2] = {w * 2, w * nslice * 2}; cuuint32_t bx[3] = {bc, 1, br};
  encode(fn, m, base, 3, d, s, bx);
}

}

extern "C" void kernel_launch(void* const* d_in, const int* in_sizes, int n_in, void* d_out, int out_size) {
  (void)in_sizes; (void)n_in; (void)out_size;
  static EncodeFn fn = nullptr;
  if (!fn) {
    void* p = nullptr;
    cudaDriverEntryPointQueryResult qr;
    cudaGetDriverEntryPoint("cuTensorMapEncodeTiled", &p, cudaEnableDefault, &qr);
    fn = (EncodeFn)p;
    cudaFuncSetAttribute(fused_h3_mlp_kernel, cudaFuncAttributeMaxDynamicSharedMemorySize, SMEM_BYTES);
  }
  void *h, *kv, *y2;
  cudaGetSymbolAddress(&y2, g_y2T);
  cudaGetSymbolAddress(&kv, g_kvT);
  cudaGetSymbolAddress(&h, g_h);
  Params P;
  const void* x = d_in[0];
  encode3(fn, &P.tm_wg, d_in[7], 224, 8, D_DIM, 64, 112);
  encode3(fn, &P.tm_wu, d_in[8], 224, 8, D_DIM, 64, 112);
  for (int i = 0; i < 2; ++i) {
    cuuint64_t d[3] = {224, 8, D_DIM}; cuuint64_t st[2] = {448, 3584}; cuuint32_t bx[3] = {32, 1, 224};
    encode(fn, i ? &P.tm_wuh : &P.tm_wgh, d_in[7 + i], 3, d, st, bx, CU_TENSOR_MAP_SWIZZLE_64B);
  }
  encode3(fn, &P.tm_hs, h, 224, 8, S_LEN, 64, 64);
  encode3(fn, &P.tm_hh, h, 32, 56, S_LEN, 64, 64);
  encode2(fn, &P.tm_hl, h, F_DIM, S_LEN, 64, 128);
  encode3(fn, &P.tm_wd, d_in[9], 112, 4, F_DIM, 64, 64);
  encode2(fn, &P.tm_xe, x, D_DIM, S_LEN, 64, 64);
  {
    cuuint64_t d[2] = {S_LEN, D_DIM}; cuuint64_t st[1] = {S_LEN * 2}; cuuint32_t bx[2] = {16, 112};
    encode(fn, &P.tm_kv, kv, 2, d, st, bx, CU_TENSOR_MAP_SWIZZLE_NONE);
  }
  {
    cuuint64_t d[3] = {64, D_DIM, 32}; cuuint64_t st[2] = {128, (cuuint64_t)D_DIM * 128}; cuuint32_t bx[3] = {64, 1, 16};
    encode(fn, &P.tm_y, y2, 3, d, st, bx, CU_TENSOR_MAP_SWIZZLE_NONE);
  }
  encode2(fn, &P.tm_yl, y2, 64, 32 * D_DIM, 64, 112);
  encode3(fn, &P.tm_out, d_out, 112, 4, S_LEN, 64, 16);
  P.k = (const __nv_bfloat16*)d_in[1];
  P.v = (const __nv_bfloat16*)d_in[2];
  P.shift_k = (const __nv_bfloat16*)d_in[3];
  P.ssm_k = (const __nv_bfloat16*)d_in[4];
  P.ssm_D = (const __nv_bfloat16*)d_in[5];
  fused_h3_mlp_kernel<<<NCTA, NTHREADS, SMEM_BYTES>>>(P);
}
```
